```python
import torch

def _softmax(x, axis=-1):
    return torch.softmax(x, dim=axis)
def _gelu(x):
    return torch.nn.functional.gelu(x, approximate="tanh")
def _silu(x):
    return torch.nn.functional.silu(x)
def _sigmoid(x):
    return torch.sigmoid(x)
def _layernorm(x, axis=-1, eps=1e-5):
    m = x.mean(dim=axis, keepdim=True)
    v = x.var(dim=axis, keepdim=True, unbiased=False)
    return (x - m) / torch.sqrt(v + eps)
def _scatter_add(tgt, idx, src, axis=0):
    return tgt.clone().index_add_(axis, idx, src)
def _segment_sum(src, seg, n):
    out = torch.zeros((n,) + src.shape[1:], dtype=src.dtype)
    return out.index_add_(0, seg, src)
def _pad(x, pw):
    flat = tuple(v for pair in reversed(pw) for v in pair)
    return torch.nn.functional.pad(x, flat)

kernel_name = 'gated_mix__ssm_conv_s4d__ssm_conv_s5__prompt'

def setup_inputs():

    _w = (lambda a: (lambda t: t.to(torch.bfloat16) if t.is_floating_point() else t)(torch.as_tensor(a)))
    def _A_setup():
        Bsz, L, D, N = 1, 2048, 576, 128
        return {
            "u": _w((lambda *s: torch.randn(*s, dtype=torch.bfloat16) * 0.05)(Bsz, L, D)),
            "log_A_real": _w((lambda *s: torch.randn(*s, dtype=torch.bfloat16) * 3.2)(D, N) * 0.5),
            "A_imag": _w((lambda *s: torch.randn(*s, dtype=torch.bfloat16) * 0.05)(D, N) * 3.14),
            "C_real": _w((lambda *s: torch.randn(*s, dtype=torch.bfloat16) * 0.1)(D, N) / N ** 0.5),
            "C_imag": _w((lambda *s: torch.randn(*s, dtype=torch.bfloat16) * 0.1)(D, N) / N ** 0.5),
            "log_dt": _w((lambda *s: torch.randn(*s, dtype=torch.bfloat16) * 0.05)(D) * 0.5 - 4.0),
            "D_skip": _w((lambda *s: torch.randn(*s, dtype=torch.bfloat16) * 0.05)(D)),
        }
    _A_in = _A_setup()

    def _B_setup():
        B, S, D = 1, 2048, 576
        P = D
        Lambda_re = -0.5 * (lambda _x: torch.exp(torch.as_tensor(_x)))((lambda *s: torch.randn(*s, dtype=torch.bfloat16) * 0.2)(P))
        Lambda_im = (lambda *s: torch.randn(*s, dtype=torch.bfloat16) * 0.4)(P) * 1.0
        B_re = (lambda *s: torch.randn(*s, dtype=torch.bfloat16) * 0.2)(P, D) * (D ** -0.5)
        B_im = (lambda *s: torch.randn(*s, dtype=torch.bfloat16) * 0.2)(P, D) * (D ** -0.5)
        C_re = (lambda *s: torch.randn(*s, dtype=torch.bfloat16) * 0.2)(D, P) * (P ** -0.5)
        C_im = (lambda *s: torch.randn(*s, dtype=torch.bfloat16) * 0.2)(D, P) * (P ** -0.5)
        log_dt = (lambda *s: torch.randn(*s, dtype=torch.bfloat16) * 0.2)(P) * 0.3 - 2.0
        Dskip = (lambda *s: torch.randn(*s, dtype=torch.bfloat16) * 0.05)(D)
        return {
            "x": _w((lambda *s: torch.randn(*s, dtype=torch.bfloat16) * 0.05)(B, S, D)),
            "Lambda_re": _w(Lambda_re),
            "Lambda_im": _w(Lambda_im),
            "B_re": _w(B_re),
            "B_im": _w(B_im),
            "C_re": _w(C_re),
            "C_im": _w(C_im),
            "log_dt": _w(log_dt),
            "Dskip": _w(Dskip),
        }
    _B_in = _B_setup()

    return {
        "A_u": _A_in["u"],
        "A_log_A_real": _A_in["log_A_real"],
        "A_A_imag": _A_in["A_imag"],
        "A_C_real": _A_in["C_real"],
        "A_C_imag": _A_in["C_imag"],
        "A_log_dt": _A_in["log_dt"],
        "A_D_skip": _A_in["D_skip"],
        "B_x": _B_in["x"],
        "B_Lambda_re": _B_in["Lambda_re"],
        "B_Lambda_im": _B_in["Lambda_im"],
        "B_B_re": _B_in["B_re"],
        "B_B_im": _B_in["B_im"],
        "B_C_re": _B_in["C_re"],
        "B_C_im": _B_in["C_im"],
        "B_log_dt": _B_in["log_dt"],
        "B_Dskip": _B_in["Dskip"],
        "gate_w": _w((lambda *s: torch.randn(*s, dtype=torch.bfloat16) * 0.05)(576) * 16.0),
    }

def reference(A_u, A_log_A_real, A_A_imag, A_C_real, A_C_imag, A_log_dt, A_D_skip, B_x, B_Lambda_re, B_Lambda_im, B_B_re, B_B_im, B_C_re, B_C_im, B_log_dt, B_Dskip, gate_w):
    def _A_ref(u, log_A_real, A_imag, C_real, C_imag, log_dt, D_skip):
        L = u.shape[1]
        dt = torch.exp(log_dt)
        A = -torch.exp(log_A_real) + 1j * A_imag
        C = (C_real + 1j * C_imag) * dt[:, None]
        pos = (lambda x, dt: x.to(dt))(torch.arange(L), log_dt.dtype)
        P = torch.exp((A * dt[:, None])[:, :, None] * pos[None, None, :])
        K = 2.0 * torch.einsum("dn,dnl->dl", C, P).real
        L2 = 2 * L
        u_t = (lambda x, *d: x.permute(*d))(u, 0, 2, 1)
        Kf = (lambda x, *a, **k: torch.fft.rfft(x.float(), *a, **k))(K, L2)
        Uf = (lambda x, *a, **k: torch.fft.rfft(x.float(), *a, **k))(u_t, L2)
        y = (lambda x, *a, **k: torch.fft.irfft(x, *a, **k).to(torch.bfloat16))(Uf * Kf[None, :, :], L2)[:, :, :L]
        y = (lambda x, *d: x.permute(*d))(y, 0, 2, 1)
        return y + u * D_skip[None, None, :]

    def _B_ref(x, Lambda_re, Lambda_im, B_re, B_im, C_re, C_im, log_dt, Dskip):
        Bsz, L, H = x.shape
        Lam = Lambda_re + 1j * Lambda_im
        Bmat = B_re + 1j * B_im
        Cmat = C_re + 1j * C_im
        dt = torch.exp(log_dt)
        Lam_bar = torch.exp(dt * Lam)
        B_bar = ((Lam_bar - 1.0) / Lam)[:, None] * Bmat
        Bu = torch.einsum("bld,pd->blp", x + 0j, B_bar)
        h = torch.zeros_like(Bu[:, 0, :])
        hs = []
        for t in range(L):
            h = Lam_bar[None, :] * h + Bu[:, t, :]
            hs.append(h)
        hseq = torch.stack(hs, 1)
        y = 2.0 * torch.einsum("blp,dp->bld", hseq, Cmat).real + x * Dskip[None, None, :]
        return y

    x = A_u
    g = _sigmoid((x * gate_w).sum(-1, keepdims=True))
    a = _A_ref(x, A_log_A_real, A_A_imag, A_C_real, A_C_imag, A_log_dt, A_D_skip)
    b = _B_ref(x, B_Lambda_re, B_Lambda_im, B_B_re, B_B_im, B_C_re, B_C_im, B_log_dt, B_Dskip)
    return g * a + (1 - g) * b
```

```cpp
#include <cuda_runtime.h>
#include <cuda_bf16.h>
#include <cuda.h>
#include <stdint.h>

namespace {

typedef __nv_bfloat16 bf16;

__device__ __forceinline__ uint32_t s2u(const void* p) { return (uint32_t)__cvta_generic_to_shared(p); }
__device__ __forceinline__ void mbar_init(uint32_t b, int c) { asm volatile("mbarrier.init.shared::cta.b64 [%0], %1;" ::"r"(b), "r"(c)); }
__device__ __forceinline__ void mbar_expect(uint32_t b, uint32_t bytes) { asm volatile("mbarrier.arrive.expect_tx.shared::cta.b64 _, [%0], %1;" ::"r"(b), "r"(bytes) : "memory"); }
__device__ __forceinline__ void mbar_arrive(uint32_t b) { asm volatile("mbarrier.arrive.shared::cta.b64 _, [%0];" ::"r"(b) : "memory"); }
#define WAIT_LIMIT (1 << 16)
#define DBG_TIMEOUT(x)
__device__ __forceinline__ void mbar_wait(uint32_t b, uint32_t parity) {
    uint32_t ok;
    int it = 0;
    do {
        asm volatile("{\n.reg .pred p;\nmbarrier.try_wait.parity.shared::cta.b64 p, [%1], %2;\nselp.u32 %0, 1, 0, p;\n}\n" : "=r"(ok) : "r"(b), "r"(parity) : "memory");
        if (++it > WAIT_LIMIT) { DBG_TIMEOUT(b); break; }
    } while (!ok);
}
__device__ __forceinline__ void fence_mbar_init() { asm volatile("fence.mbarrier_init.release.cluster;" ::: "memory"); }
__device__ __forceinline__ void fence_async_smem() { asm volatile("fence.proxy.async.shared::cta;" ::: "memory"); }
__device__ __forceinline__ void fence_async_all() { asm volatile("fence.proxy.async;" ::: "memory"); }
__device__ __forceinline__ void tma_ld2(uint32_t dst, const CUtensorMap* m, int c0, int c1, uint32_t bar) {
    asm volatile("cp.async.bulk.tensor.2d.shared::cluster.global.mbarrier::complete_tx::bytes [%0], [%1, {%3,%4}], [%2];" ::"r"(dst), "l"(m), "r"(bar), "r"(c0), "r"(c1) : "memory");
}
__device__ __forceinline__ void tma_ld4(uint32_t dst, const CUtensorMap* m, int c0, int c1, int c2, int c3, uint32_t bar) {
    asm volatile("cp.async.bulk.tensor.4d.shared::cluster.global.mbarrier::complete_tx::bytes [%0], [%1, {%3,%4,%5,%6}], [%2];" ::"r"(dst), "l"(m), "r"(bar), "r"(c0), "r"(c1), "r"(c2), "r"(c3) : "memory");
}
__device__ __forceinline__ void tma_st4(const CUtensorMap* m, uint32_t src, int c0, int c1, int c2, int c3) {
    asm volatile("cp.async.bulk.tensor.4d.global.shared::cta.bulk_group [%0, {%2,%3,%4,%5}], [%1];" ::"l"(m), "r"(src), "r"(c0), "r"(c1), "r"(c2), "r"(c3) : "memory");
}
__device__ __forceinline__ void bulk_st(void* gdst, uint32_t src, uint32_t bytes) {
    asm volatile("cp.async.bulk.global.shared::cta.bulk_group [%0], [%1], %2;" ::"l"(gdst), "r"(src), "r"(bytes) : "memory");
}
__device__ __forceinline__ void bulk_ld(uint32_t dst, const void* gsrc, uint32_t bytes, uint32_t bar) {
    asm volatile("cp.async.bulk.shared::cluster.global.mbarrier::complete_tx::bytes [%0], [%1], %2, [%3];" ::"r"(dst), "l"(gsrc), "r"(bytes), "r"(bar) : "memory");
}
__device__ __forceinline__ void bulk_commit() { asm volatile("cp.async.bulk.commit_group;" ::: "memory"); }
__device__ __forceinline__ void bulk_wait0() { asm volatile("cp.async.bulk.wait_group 0;" ::: "memory"); }
__device__ __forceinline__ void bulk_wait_read0() { asm volatile("cp.async.bulk.wait_group.read 0;" ::: "memory"); }
__device__ __forceinline__ void prefetch_map(const CUtensorMap* m) { asm volatile("prefetch.tensormap [%0];" ::"l"(m) : "memory"); }
__device__ __forceinline__ void wg_fence() { asm volatile("wgmma.fence.sync.aligned;" ::: "memory"); }
__device__ __forceinline__ void wg_commit() { asm volatile("wgmma.commit_group.sync.aligned;" ::: "memory"); }
template <int N> __device__ __forceinline__ void wg_wait() { asm volatile("wgmma.wait_group.sync.aligned %0;" ::"n"(N) : "memory"); }
__device__ __forceinline__ void bar_sync(int id, int n) { asm volatile("bar.sync %0, %1;" ::"r"(id), "r"(n) : "memory"); }
__device__ __forceinline__ void bar_arrive(int id, int n) { asm volatile("bar.arrive %0, %1;" ::"r"(id), "r"(n) : "memory"); }
__device__ __forceinline__ uint64_t mkdesc(uint32_t addr, uint32_t lbo, uint32_t sbo, uint32_t swz) {
    return (uint64_t)((addr & 0x3FFFF) >> 4) | ((uint64_t)(lbo >> 4) << 16) | ((uint64_t)(sbo >> 4) << 32) | ((uint64_t)swz << 62);
}
__device__ __forceinline__ uint32_t pack_bf16(float lo, float hi) {
    uint32_t r;
    asm("cvt.rn.bf16x2.f32 %0, %1, %2;" : "=r"(r) : "f"(hi), "f"(lo));
    return r;
}
__device__ __forceinline__ float bf16r(float x) { return __bfloat162float(__float2bfloat16_rn(x)); }
__device__ __forceinline__ float bflo(uint32_t v) { return __uint_as_float(v << 16); }
__device__ __forceinline__ float bfhi(uint32_t v) { return __uint_as_float(v & 0xffff0000u); }
__device__ __forceinline__ float ldbf(const bf16* p) { return __bfloat162float(*p); }
__device__ __forceinline__ void st_pkt(void* p, float re, float im, uint32_t tag) {
    uint64_t a = ((uint64_t)tag << 32) | __float_as_uint(re), b = ((uint64_t)tag << 32) | __float_as_uint(im);
    asm volatile("st.relaxed.gpu.global.v2.b64 [%0], {%1,%2};" ::"l"(p), "l"(a), "l"(b) : "memory");
}
__device__ __forceinline__ void ld_pkt(const void* p, uint64_t& a, uint64_t& b) {
    asm volatile("ld.relaxed.gpu.global.v2.b64 {%0,%1}, [%2];" : "=l"(a), "=l"(b) : "l"(p) : "memory");
}
__device__ __forceinline__ uint32_t ld_relaxed(const uint32_t* p) {
    uint32_t v;
    asm volatile("ld.relaxed.gpu.global.u32 %0, [%1];" : "=r"(v) : "l"(p) : "memory");
    return v;
}
__device__ __forceinline__ uint32_t ld_acquire(const uint32_t* p) {
    uint32_t v;
    asm volatile("ld.acquire.gpu.global.u32 %0, [%1];" : "=r"(v) : "l"(p) : "memory");
    return v;
}
__device__ __forceinline__ void red_release_add(uint32_t* p, uint32_t v) {
    asm volatile("red.release.gpu.global.add.u32 [%0], %1;" ::"l"(p), "r"(v) : "memory");
}

#define PROF(slot)
#define PROFG(slot)
template<int N> struct WgRS;
template<int TA, int TB> __device__ __forceinline__ void wgmma_ss_n160(float (&d)[80], uint64_t da, uint64_t db, int sd) {
  asm volatile("{\n.reg .pred p;\nsetp.ne.b32 p, %82, 0;\n"
    "wgmma.mma_async.sync.aligned.m64n160k16.f32.bf16.bf16 {%0,%1,%2,%3,%4,%5,%6,%7,%8,%9,%10,%11,%12,%13,%14,%15,%16,%17,%18,%19,%20,%21,%22,%23,%24,%25,%26,%27,%28,%29,%30,%31,%32,%33,%34,%35,%36,%37,%38,%39,%40,%41,%42,%43,%44,%45,%46,%47,%48,%49,%50,%51,%52,%53,%54,%55,%56,%57,%58,%59,%60,%61,%62,%63,%64,%65,%66,%67,%68,%69,%70,%71,%72,%73,%74,%75,%76,%77,%78,%79}, %80, %81, p, 1, 1, %83, %84;\n}\n"
    : "+f"(d[0]),"+f"(d[1]),"+f"(d[2]),"+f"(d[3]),"+f"(d[4]),"+f"(d[5]),"+f"(d[6]),"+f"(d[7]),"+f"(d[8]),"+f"(d[9]),"+f"(d[10]),"+f"(d[11]),"+f"(d[12]),"+f"(d[13]),"+f"(d[14]),"+f"(d[15]),"+f"(d[16]),"+f"(d[17]),"+f"(d[18]),"+f"(d[19]),"+f"(d[20]),"+f"(d[21]),"+f"(d[22]),"+f"(d[23]),"+f"(d[24]),"+f"(d[25]),"+f"(d[26]),"+f"(d[27]),"+f"(d[28]),"+f"(d[29]),"+f"(d[30]),"+f"(d[31]),"+f"(d[32]),"+f"(d[33]),"+f"(d[34]),"+f"(d[35]),"+f"(d[36]),"+f"(d[37]),"+f"(d[38]),"+f"(d[39]),"+f"(d[40]),"+f"(d[41]),"+f"(d[42]),"+f"(d[43]),"+f"(d[44]),"+f"(d[45]),"+f"(d[46]),"+f"(d[47]),"+f"(d[48]),"+f"(d[49]),"+f"(d[50]),"+f"(d[51]),"+f"(d[52]),"+f"(d[53]),"+f"(d[54]),"+f"(d[55]),"+f"(d[56]),"+f"(d[57]),"+f"(d[58]),"+f"(d[59]),"+f"(d[60]),"+f"(d[61]),"+f"(d[62]),"+f"(d[63]),"+f"(d[64]),"+f"(d[65]),"+f"(d[66]),"+f"(d[67]),"+f"(d[68]),"+f"(d[69]),"+f"(d[70]),"+f"(d[71]),"+f"(d[72]),"+f"(d[73]),"+f"(d[74]),"+f"(d[75]),"+f"(d[76]),"+f"(d[77]),"+f"(d[78]),"+f"(d[79])
    : "l"(da),"l"(db),"r"(sd),"n"(TA),"n"(TB));
}
template<int TA, int TB> __device__ __forceinline__ void wgmma_ss_n152(float (&d)[76], uint64_t da, uint64_t db, int sd) {
  asm volatile("{\n.reg .pred p;\nsetp.ne.b32 p, %78, 0;\n"
    "wgmma.mma_async.sync.aligned.m64n152k16.f32.bf16.bf16 {%0,%1,%2,%3,%4,%5,%6,%7,%8,%9,%10,%11,%12,%13,%14,%15,%16,%17,%18,%19,%20,%21,%22,%23,%24,%25,%26,%27,%28,%29,%30,%31,%32,%33,%34,%35,%36,%37,%38,%39,%40,%41,%42,%43,%44,%45,%46,%47,%48,%49,%50,%51,%52,%53,%54,%55,%56,%57,%58,%59,%60,%61,%62,%63,%64,%65,%66,%67,%68,%69,%70,%71,%72,%73,%74,%75}, %76, %77, p, 1, 1, %79, %80;\n}\n"
    : "+f"(d[0]),"+f"(d[1]),"+f"(d[2]),"+f"(d[3]),"+f"(d[4]),"+f"(d[5]),"+f"(d[6]),"+f"(d[7]),"+f"(d[8]),"+f"(d[9]),"+f"(d[10]),"+f"(d[11]),"+f"(d[12]),"+f"(d[13]),"+f"(d[14]),"+f"(d[15]),"+f"(d[16]),"+f"(d[17]),"+f"(d[18]),"+f"(d[19]),"+f"(d[20]),"+f"(d[21]),"+f"(d[22]),"+f"(d[23]),"+f"(d[24]),"+f"(d[25]),"+f"(d[26]),"+f"(d[27]),"+f"(d[28]),"+f"(d[29]),"+f"(d[30]),"+f"(d[31]),"+f"(d[32]),"+f"(d[33]),"+f"(d[34]),"+f"(d[35]),"+f"(d[36]),"+f"(d[37]),"+f"(d[38]),"+f"(d[39]),"+f"(d[40]),"+f"(d[41]),"+f"(d[42]),"+f"(d[43]),"+f"(d[44]),"+f"(d[45]),"+f"(d[46]),"+f"(d[47]),"+f"(d[48]),"+f"(d[49]),"+f"(d[50]),"+f"(d[51]),"+f"(d[52]),"+f"(d[53]),"+f"(d[54]),"+f"(d[55]),"+f"(d[56]),"+f"(d[57]),"+f"(d[58]),"+f"(d[59]),"+f"(d[60]),"+f"(d[61]),"+f"(d[62]),"+f"(d[63]),"+f"(d[64]),"+f"(d[65]),"+f"(d[66]),"+f"(d[67]),"+f"(d[68]),"+f"(d[69]),"+f"(d[70]),"+f"(d[71]),"+f"(d[72]),"+f"(d[73]),"+f"(d[74]),"+f"(d[75])
    : "l"(da),"l"(db),"r"(sd),"n"(TA),"n"(TB));
}
template<int TA, int TB> __device__ __forceinline__ void wgmma_ss_n144(float (&d)[72], uint64_t da, uint64_t db, int sd) {
  asm volatile("{\n.reg .pred p;\nsetp.ne.b32 p, %74, 0;\n"
    "wgmma.mma_async.sync.aligned.m64n144k16.f32.bf16.bf16 {%0,%1,%2,%3,%4,%5,%6,%7,%8,%9,%10,%11,%12,%13,%14,%15,%16,%17,%18,%19,%20,%21,%22,%23,%24,%25,%26,%27,%28,%29,%30,%31,%32,%33,%34,%35,%36,%37,%38,%39,%40,%41,%42,%43,%44,%45,%46,%47,%48,%49,%50,%51,%52,%53,%54,%55,%56,%57,%58,%59,%60,%61,%62,%63,%64,%65,%66,%67,%68,%69,%70,%71}, %72, %73, p, 1, 1, %75, %76;\n}\n"
    : "+f"(d[0]),"+f"(d[1]),"+f"(d[2]),"+f"(d[3]),"+f"(d[4]),"+f"(d[5]),"+f"(d[6]),"+f"(d[7]),"+f"(d[8]),"+f"(d[9]),"+f"(d[10]),"+f"(d[11]),"+f"(d[12]),"+f"(d[13]),"+f"(d[14]),"+f"(d[15]),"+f"(d[16]),"+f"(d[17]),"+f"(d[18]),"+f"(d[19]),"+f"(d[20]),"+f"(d[21]),"+f"(d[22]),"+f"(d[23]),"+f"(d[24]),"+f"(d[25]),"+f"(d[26]),"+f"(d[27]),"+f"(d[28]),"+f"(d[29]),"+f"(d[30]),"+f"(d[31]),"+f"(d[32]),"+f"(d[33]),"+f"(d[34]),"+f"(d[35]),"+f"(d[36]),"+f"(d[37]),"+f"(d[38]),"+f"(d[39]),"+f"(d[40]),"+f"(d[41]),"+f"(d[42]),"+f"(d[43]),"+f"(d[44]),"+f"(d[45]),"+f"(d[46]),"+f"(d[47]),"+f"(d[48]),"+f"(d[49]),"+f"(d[50]),"+f"(d[51]),"+f"(d[52]),"+f"(d[53]),"+f"(d[54]),"+f"(d[55]),"+f"(d[56]),"+f"(d[57]),"+f"(d[58]),"+f"(d[59]),"+f"(d[60]),"+f"(d[61]),"+f"(d[62]),"+f"(d[63]),"+f"(d[64]),"+f"(d[65]),"+f"(d[66]),"+f"(d[67]),"+f"(d[68]),"+f"(d[69]),"+f"(d[70]),"+f"(d[71])
    : "l"(da),"l"(db),"r"(sd),"n"(TA),"n"(TB));
}
template<> struct WgRS<8> { static __device__ __forceinline__ void go(float* d, const uint32_t* a, uint64_t db) {
  asm volatile("wgmma.mma_async.sync.aligned.m64n8k16.f32.bf16.bf16 {%0,%1,%2,%3}, {%4,%5,%6,%7}, %8, 1, 1, 1, 0;\n"
    : "+f"(d[0]),"+f"(d[1]),"+f"(d[2]),"+f"(d[3])
    : "r"(a[0]),"r"(a[1]),"r"(a[2]),"r"(a[3]),"l"(db));
} };
template<> struct WgRS<16> { static __device__ __forceinline__ void go(float* d, const uint32_t* a, uint64_t db) {
  asm volatile("wgmma.mma_async.sync.aligned.m64n16k16.f32.bf16.bf16 {%0,%1,%2,%3,%4,%5,%6,%7}, {%8,%9,%10,%11}, %12, 1, 1, 1, 0;\n"
    : "+f"(d[0]),"+f"(d[1]),"+f"(d[2]),"+f"(d[3]),"+f"(d[4]),"+f"(d[5]),"+f"(d[6]),"+f"(d[7])
    : "r"(a[0]),"r"(a[1]),"r"(a[2]),"r"(a[3]),"l"(db));
} };
template<> struct WgRS<24> { static __device__ __forceinline__ void go(float* d, const uint32_t* a, uint64_t db) {
  asm volatile("wgmma.mma_async.sync.aligned.m64n24k16.f32.bf16.bf16 {%0,%1,%2,%3,%4,%5,%6,%7,%8,%9,%10,%11}, {%12,%13,%14,%15}, %16, 1, 1, 1, 0;\n"
    : "+f"(d[0]),"+f"(d[1]),"+f"(d[2]),"+f"(d[3]),"+f"(d[4]),"+f"(d[5]),"+f"(d[6]),"+f"(d[7]),"+f"(d[8]),"+f"(d[9]),"+f"(d[10]),"+f"(d[11])
    : "r"(a[0]),"r"(a[1]),"r"(a[2]),"r"(a[3]),"l"(db));
} };
template<> struct WgRS<32> { static __device__ __forceinline__ void go(float* d, const uint32_t* a, uint64_t db) {
  asm volatile("wgmma.mma_async.sync.aligned.m64n32k16.f32.bf16.bf16 {%0,%1,%2,%3,%4,%5,%6,%7,%8,%9,%10,%11,%12,%13,%14,%15}, {%16,%17,%18,%19}, %20, 1, 1, 1, 0;\n"
    : "+f"(d[0]),"+f"(d[1]),"+f"(d[2]),"+f"(d[3]),"+f"(d[4]),"+f"(d[5]),"+f"(d[6]),"+f"(d[7]),"+f"(d[8]),"+f"(d[9]),"+f"(d[10]),"+f"(d[11]),"+f"(d[12]),"+f"(d[13]),"+f"(d[14]),"+f"(d[15])
    : "r"(a[0]),"r"(a[1]),"r"(a[2]),"r"(a[3]),"l"(db));
} };
template<> struct WgRS<40> { static __device__ __forceinline__ void go(float* d, const uint32_t* a, uint64_t db) {
  asm volatile("wgmma.mma_async.sync.aligned.m64n40k16.f32.bf16.bf16 {%0,%1,%2,%3,%4,%5,%6,%7,%8,%9,%10,%11,%12,%13,%14,%15,%16,%17,%18,%19}, {%20,%21,%22,%23}, %24, 1, 1, 1, 0;\n"
    : "+f"(d[0]),"+f"(d[1]),"+f"(d[2]),"+f"(d[3]),"+f"(d[4]),"+f"(d[5]),"+f"(d[6]),"+f"(d[7]),"+f"(d[8]),"+f"(d[9]),"+f"(d[10]),"+f"(d[11]),"+f"(d[12]),"+f"(d[13]),"+f"(d[14]),"+f"(d[15]),"+f"(d[16]),"+f"(d[17]),"+f"(d[18]),"+f"(d[19])
    : "r"(a[0]),"r"(a[1]),"r"(a[2]),"r"(a[3]),"l"(db));
} };
template<> struct WgRS<48> { static __device__ __forceinline__ void go(float* d, const uint32_t* a, uint64_t db) {
  asm volatile("wgmma.mma_async.sync.aligned.m64n48k16.f32.bf16.bf16 {%0,%1,%2,%3,%4,%5,%6,%7,%8,%9,%10,%11,%12,%13,%14,%15,%16,%17,%18,%19,%20,%21,%22,%23}, {%24,%25,%26,%27}, %28, 1, 1, 1, 0;\n"
    : "+f"(d[0]),"+f"(d[1]),"+f"(d[2]),"+f"(d[3]),"+f"(d[4]),"+f"(d[5]),"+f"(d[6]),"+f"(d[7]),"+f"(d[8]),"+f"(d[9]),"+f"(d[10]),"+f"(d[11]),"+f"(d[12]),"+f"(d[13]),"+f"(d[14]),"+f"(d[15]),"+f"(d[16]),"+f"(d[17]),"+f"(d[18]),"+f"(d[19]),"+f"(d[20]),"+f"(d[21]),"+f"(d[22]),"+f"(d[23])
    : "r"(a[0]),"r"(a[1]),"r"(a[2]),"r"(a[3]),"l"(db));
} };
template<> struct WgRS<56> { static __device__ __forceinline__ void go(float* d, const uint32_t* a, uint64_t db) {
  asm volatile("wgmma.mma_async.sync.aligned.m64n56k16.f32.bf16.bf16 {%0,%1,%2,%3,%4,%5,%6,%7,%8,%9,%10,%11,%12,%13,%14,%15,%16,%17,%18,%19,%20,%21,%22,%23,%24,%25,%26,%27}, {%28,%29,%30,%31}, %32, 1, 1, 1, 0;\n"
    : "+f"(d[0]),"+f"(d[1]),"+f"(d[2]),"+f"(d[3]),"+f"(d[4]),"+f"(d[5]),"+f"(d[6]),"+f"(d[7]),"+f"(d[8]),"+f"(d[9]),"+f"(d[10]),"+f"(d[11]),"+f"(d[12]),"+f"(d[13]),"+f"(d[14]),"+f"(d[15]),"+f"(d[16]),"+f"(d[17]),"+f"(d[18]),"+f"(d[19]),"+f"(d[20]),"+f"(d[21]),"+f"(d[22]),"+f"(d[23]),"+f"(d[24]),"+f"(d[25]),"+f"(d[26]),"+f"(d[27])
    : "r"(a[0]),"r"(a[1]),"r"(a[2]),"r"(a[3]),"l"(db));
} };
template<> struct WgRS<64> { static __device__ __forceinline__ void go(float* d, const uint32_t* a, uint64_t db) {
  asm volatile("wgmma.mma_async.sync.aligned.m64n64k16.f32.bf16.bf16 {%0,%1,%2,%3,%4,%5,%6,%7,%8,%9,%10,%11,%12,%13,%14,%15,%16,%17,%18,%19,%20,%21,%22,%23,%24,%25,%26,%27,%28,%29,%30,%31}, {%32,%33,%34,%35}, %36, 1, 1, 1, 0;\n"
    : "+f"(d[0]),"+f"(d[1]),"+f"(d[2]),"+f"(d[3]),"+f"(d[4]),"+f"(d[5]),"+f"(d[6]),"+f"(d[7]),"+f"(d[8]),"+f"(d[9]),"+f"(d[10]),"+f"(d[11]),"+f"(d[12]),"+f"(d[13]),"+f"(d[14]),"+f"(d[15]),"+f"(d[16]),"+f"(d[17]),"+f"(d[18]),"+f"(d[19]),"+f"(d[20]),"+f"(d[21]),"+f"(d[22]),"+f"(d[23]),"+f"(d[24]),"+f"(d[25]),"+f"(d[26]),"+f"(d[27]),"+f"(d[28]),"+f"(d[29]),"+f"(d[30]),"+f"(d[31])
    : "r"(a[0]),"r"(a[1]),"r"(a[2]),"r"(a[3]),"l"(db));
} };
template<> struct WgRS<72> { static __device__ __forceinline__ void go(float* d, const uint32_t* a, uint64_t db) {
  asm volatile("wgmma.mma_async.sync.aligned.m64n72k16.f32.bf16.bf16 {%0,%1,%2,%3,%4,%5,%6,%7,%8,%9,%10,%11,%12,%13,%14,%15,%16,%17,%18,%19,%20,%21,%22,%23,%24,%25,%26,%27,%28,%29,%30,%31,%32,%33,%34,%35}, {%36,%37,%38,%39}, %40, 1, 1, 1, 0;\n"
    : "+f"(d[0]),"+f"(d[1]),"+f"(d[2]),"+f"(d[3]),"+f"(d[4]),"+f"(d[5]),"+f"(d[6]),"+f"(d[7]),"+f"(d[8]),"+f"(d[9]),"+f"(d[10]),"+f"(d[11]),"+f"(d[12]),"+f"(d[13]),"+f"(d[14]),"+f"(d[15]),"+f"(d[16]),"+f"(d[17]),"+f"(d[18]),"+f"(d[19]),"+f"(d[20]),"+f"(d[21]),"+f"(d[22]),"+f"(d[23]),"+f"(d[24]),"+f"(d[25]),"+f"(d[26]),"+f"(d[27]),"+f"(d[28]),"+f"(d[29]),"+f"(d[30]),"+f"(d[31]),"+f"(d[32]),"+f"(d[33]),"+f"(d[34]),"+f"(d[35])
    : "r"(a[0]),"r"(a[1]),"r"(a[2]),"r"(a[3]),"l"(db));
} };
template<> struct WgRS<80> { static __device__ __forceinline__ void go(float* d, const uint32_t* a, uint64_t db) {
  asm volatile("wgmma.mma_async.sync.aligned.m64n80k16.f32.bf16.bf16 {%0,%1,%2,%3,%4,%5,%6,%7,%8,%9,%10,%11,%12,%13,%14,%15,%16,%17,%18,%19,%20,%21,%22,%23,%24,%25,%26,%27,%28,%29,%30,%31,%32,%33,%34,%35,%36,%37,%38,%39}, {%40,%41,%42,%43}, %44, 1, 1, 1, 0;\n"
    : "+f"(d[0]),"+f"(d[1]),"+f"(d[2]),"+f"(d[3]),"+f"(d[4]),"+f"(d[5]),"+f"(d[6]),"+f"(d[7]),"+f"(d[8]),"+f"(d[9]),"+f"(d[10]),"+f"(d[11]),"+f"(d[12]),"+f"(d[13]),"+f"(d[14]),"+f"(d[15]),"+f"(d[16]),"+f"(d[17]),"+f"(d[18]),"+f"(d[19]),"+f"(d[20]),"+f"(d[21]),"+f"(d[22]),"+f"(d[23]),"+f"(d[24]),"+f"(d[25]),"+f"(d[26]),"+f"(d[27]),"+f"(d[28]),"+f"(d[29]),"+f"(d[30]),"+f"(d[31]),"+f"(d[32]),"+f"(d[33]),"+f"(d[34]),"+f"(d[35]),"+f"(d[36]),"+f"(d[37]),"+f"(d[38]),"+f"(d[39])
    : "r"(a[0]),"r"(a[1]),"r"(a[2]),"r"(a[3]),"l"(db));
} };
template<> struct WgRS<88> { static __device__ __forceinline__ void go(float* d, const uint32_t* a, uint64_t db) {
  asm volatile("wgmma.mma_async.sync.aligned.m64n88k16.f32.bf16.bf16 {%0,%1,%2,%3,%4,%5,%6,%7,%8,%9,%10,%11,%12,%13,%14,%15,%16,%17,%18,%19,%20,%21,%22,%23,%24,%25,%26,%27,%28,%29,%30,%31,%32,%33,%34,%35,%36,%37,%38,%39,%40,%41,%42,%43}, {%44,%45,%46,%47}, %48, 1, 1, 1, 0;\n"
    : "+f"(d[0]),"+f"(d[1]),"+f"(d[2]),"+f"(d[3]),"+f"(d[4]),"+f"(d[5]),"+f"(d[6]),"+f"(d[7]),"+f"(d[8]),"+f"(d[9]),"+f"(d[10]),"+f"(d[11]),"+f"(d[12]),"+f"(d[13]),"+f"(d[14]),"+f"(d[15]),"+f"(d[16]),"+f"(d[17]),"+f"(d[18]),"+f"(d[19]),"+f"(d[20]),"+f"(d[21]),"+f"(d[22]),"+f"(d[23]),"+f"(d[24]),"+f"(d[25]),"+f"(d[26]),"+f"(d[27]),"+f"(d[28]),"+f"(d[29]),"+f"(d[30]),"+f"(d[31]),"+f"(d[32]),"+f"(d[33]),"+f"(d[34]),"+f"(d[35]),"+f"(d[36]),"+f"(d[37]),"+f"(d[38]),"+f"(d[39]),"+f"(d[40]),"+f"(d[41]),"+f"(d[42]),"+f"(d[43])
    : "r"(a[0]),"r"(a[1]),"r"(a[2]),"r"(a[3]),"l"(db));
} };
template<> struct WgRS<96> { static __device__ __forceinline__ void go(float* d, const uint32_t* a, uint64_t db) {
  asm volatile("wgmma.mma_async.sync.aligned.m64n96k16.f32.bf16.bf16 {%0,%1,%2,%3,%4,%5,%6,%7,%8,%9,%10,%11,%12,%13,%14,%15,%16,%17,%18,%19,%20,%21,%22,%23,%24,%25,%26,%27,%28,%29,%30,%31,%32,%33,%34,%35,%36,%37,%38,%39,%40,%41,%42,%43,%44,%45,%46,%47}, {%48,%49,%50,%51}, %52, 1, 1, 1, 0;\n"
    : "+f"(d[0]),"+f"(d[1]),"+f"(d[2]),"+f"(d[3]),"+f"(d[4]),"+f"(d[5]),"+f"(d[6]),"+f"(d[7]),"+f"(d[8]),"+f"(d[9]),"+f"(d[10]),"+f"(d[11]),"+f"(d[12]),"+f"(d[13]),"+f"(d[14]),"+f"(d[15]),"+f"(d[16]),"+f"(d[17]),"+f"(d[18]),"+f"(d[19]),"+f"(d[20]),"+f"(d[21]),"+f"(d[22]),"+f"(d[23]),"+f"(d[24]),"+f"(d[25]),"+f"(d[26]),"+f"(d[27]),"+f"(d[28]),"+f"(d[29]),"+f"(d[30]),"+f"(d[31]),"+f"(d[32]),"+f"(d[33]),"+f"(d[34]),"+f"(d[35]),"+f"(d[36]),"+f"(d[37]),"+f"(d[38]),"+f"(d[39]),"+f"(d[40]),"+f"(d[41]),"+f"(d[42]),"+f"(d[43]),"+f"(d[44]),"+f"(d[45]),"+f"(d[46]),"+f"(d[47])
    : "r"(a[0]),"r"(a[1]),"r"(a[2]),"r"(a[3]),"l"(db));
} };
template<> struct WgRS<104> { static __device__ __forceinline__ void go(float* d, const uint32_t* a, uint64_t db) {
  asm volatile("wgmma.mma_async.sync.aligned.m64n104k16.f32.bf16.bf16 {%0,%1,%2,%3,%4,%5,%6,%7,%8,%9,%10,%11,%12,%13,%14,%15,%16,%17,%18,%19,%20,%21,%22,%23,%24,%25,%26,%27,%28,%29,%30,%31,%32,%33,%34,%35,%36,%37,%38,%39,%40,%41,%42,%43,%44,%45,%46,%47,%48,%49,%50,%51}, {%52,%53,%54,%55}, %56, 1, 1, 1, 0;\n"
    : "+f"(d[0]),"+f"(d[1]),"+f"(d[2]),"+f"(d[3]),"+f"(d[4]),"+f"(d[5]),"+f"(d[6]),"+f"(d[7]),"+f"(d[8]),"+f"(d[9]),"+f"(d[10]),"+f"(d[11]),"+f"(d[12]),"+f"(d[13]),"+f"(d[14]),"+f"(d[15]),"+f"(d[16]),"+f"(d[17]),"+f"(d[18]),"+f"(d[19]),"+f"(d[20]),"+f"(d[21]),"+f"(d[22]),"+f"(d[23]),"+f"(d[24]),"+f"(d[25]),"+f"(d[26]),"+f"(d[27]),"+f"(d[28]),"+f"(d[29]),"+f"(d[30]),"+f"(d[31]),"+f"(d[32]),"+f"(d[33]),"+f"(d[34]),"+f"(d[35]),"+f"(d[36]),"+f"(d[37]),"+f"(d[38]),"+f"(d[39]),"+f"(d[40]),"+f"(d[41]),"+f"(d[42]),"+f"(d[43]),"+f"(d[44]),"+f"(d[45]),"+f"(d[46]),"+f"(d[47]),"+f"(d[48]),"+f"(d[49]),"+f"(d[50]),"+f"(d[51])
    : "r"(a[0]),"r"(a[1]),"r"(a[2]),"r"(a[3]),"l"(db));
} };
template<> struct WgRS<112> { static __device__ __forceinline__ void go(float* d, const uint32_t* a, uint64_t db) {
  asm volatile("wgmma.mma_async.sync.aligned.m64n112k16.f32.bf16.bf16 {%0,%1,%2,%3,%4,%5,%6,%7,%8,%9,%10,%11,%12,%13,%14,%15,%16,%17,%18,%19,%20,%21,%22,%23,%24,%25,%26,%27,%28,%29,%30,%31,%32,%33,%34,%35,%36,%37,%38,%39,%40,%41,%42,%43,%44,%45,%46,%47,%48,%49,%50,%51,%52,%53,%54,%55}, {%56,%57,%58,%59}, %60, 1, 1, 1, 0;\n"
    : "+f"(d[0]),"+f"(d[1]),"+f"(d[2]),"+f"(d[3]),"+f"(d[4]),"+f"(d[5]),"+f"(d[6]),"+f"(d[7]),"+f"(d[8]),"+f"(d[9]),"+f"(d[10]),"+f"(d[11]),"+f"(d[12]),"+f"(d[13]),"+f"(d[14]),"+f"(d[15]),"+f"(d[16]),"+f"(d[17]),"+f"(d[18]),"+f"(d[19]),"+f"(d[20]),"+f"(d[21]),"+f"(d[22]),"+f"(d[23]),"+f"(d[24]),"+f"(d[25]),"+f"(d[26]),"+f"(d[27]),"+f"(d[28]),"+f"(d[29]),"+f"(d[30]),"+f"(d[31]),"+f"(d[32]),"+f"(d[33]),"+f"(d[34]),"+f"(d[35]),"+f"(d[36]),"+f"(d[37]),"+f"(d[38]),"+f"(d[39]),"+f"(d[40]),"+f"(d[41]),"+f"(d[42]),"+f"(d[43]),"+f"(d[44]),"+f"(d[45]),"+f"(d[46]),"+f"(d[47]),"+f"(d[48]),"+f"(d[49]),"+f"(d[50]),"+f"(d[51]),"+f"(d[52]),"+f"(d[53]),"+f"(d[54]),"+f"(d[55])
    : "r"(a[0]),"r"(a[1]),"r"(a[2]),"r"(a[3]),"l"(db));
} };
template<> struct WgRS<120> { static __device__ __forceinline__ void go(float* d, const uint32_t* a, uint64_t db) {
  asm volatile("wgmma.mma_async.sync.aligned.m64n120k16.f32.bf16.bf16 {%0,%1,%2,%3,%4,%5,%6,%7,%8,%9,%10,%11,%12,%13,%14,%15,%16,%17,%18,%19,%20,%21,%22,%23,%24,%25,%26,%27,%28,%29,%30,%31,%32,%33,%34,%35,%36,%37,%38,%39,%40,%41,%42,%43,%44,%45,%46,%47,%48,%49,%50,%51,%52,%53,%54,%55,%56,%57,%58,%59}, {%60,%61,%62,%63}, %64, 1, 1, 1, 0;\n"
    : "+f"(d[0]),"+f"(d[1]),"+f"(d[2]),"+f"(d[3]),"+f"(d[4]),"+f"(d[5]),"+f"(d[6]),"+f"(d[7]),"+f"(d[8]),"+f"(d[9]),"+f"(d[10]),"+f"(d[11]),"+f"(d[12]),"+f"(d[13]),"+f"(d[14]),"+f"(d[15]),"+f"(d[16]),"+f"(d[17]),"+f"(d[18]),"+f"(d[19]),"+f"(d[20]),"+f"(d[21]),"+f"(d[22]),"+f"(d[23]),"+f"(d[24]),"+f"(d[25]),"+f"(d[26]),"+f"(d[27]),"+f"(d[28]),"+f"(d[29]),"+f"(d[30]),"+f"(d[31]),"+f"(d[32]),"+f"(d[33]),"+f"(d[34]),"+f"(d[35]),"+f"(d[36]),"+f"(d[37]),"+f"(d[38]),"+f"(d[39]),"+f"(d[40]),"+f"(d[41]),"+f"(d[42]),"+f"(d[43]),"+f"(d[44]),"+f"(d[45]),"+f"(d[46]),"+f"(d[47]),"+f"(d[48]),"+f"(d[49]),"+f"(d[50]),"+f"(d[51]),"+f"(d[52]),"+f"(d[53]),"+f"(d[54]),"+f"(d[55]),"+f"(d[56]),"+f"(d[57]),"+f"(d[58]),"+f"(d[59])
    : "r"(a[0]),"r"(a[1]),"r"(a[2]),"r"(a[3]),"l"(db));
} };
template<> struct WgRS<128> { static __device__ __forceinline__ void go(float* d, const uint32_t* a, uint64_t db) {
  asm volatile("wgmma.mma_async.sync.aligned.m64n128k16.f32.bf16.bf16 {%0,%1,%2,%3,%4,%5,%6,%7,%8,%9,%10,%11,%12,%13,%14,%15,%16,%17,%18,%19,%20,%21,%22,%23,%24,%25,%26,%27,%28,%29,%30,%31,%32,%33,%34,%35,%36,%37,%38,%39,%40,%41,%42,%43,%44,%45,%46,%47,%48,%49,%50,%51,%52,%53,%54,%55,%56,%57,%58,%59,%60,%61,%62,%63}, {%64,%65,%66,%67}, %68, 1, 1, 1, 0;\n"
    : "+f"(d[0]),"+f"(d[1]),"+f"(d[2]),"+f"(d[3]),"+f"(d[4]),"+f"(d[5]),"+f"(d[6]),"+f"(d[7]),"+f"(d[8]),"+f"(d[9]),"+f"(d[10]),"+f"(d[11]),"+f"(d[12]),"+f"(d[13]),"+f"(d[14]),"+f"(d[15]),"+f"(d[16]),"+f"(d[17]),"+f"(d[18]),"+f"(d[19]),"+f"(d[20]),"+f"(d[21]),"+f"(d[22]),"+f"(d[23]),"+f"(d[24]),"+f"(d[25]),"+f"(d[26]),"+f"(d[27]),"+f"(d[28]),"+f"(d[29]),"+f"(d[30]),"+f"(d[31]),"+f"(d[32]),"+f"(d[33]),"+f"(d[34]),"+f"(d[35]),"+f"(d[36]),"+f"(d[37]),"+f"(d[38]),"+f"(d[39]),"+f"(d[40]),"+f"(d[41]),"+f"(d[42]),"+f"(d[43]),"+f"(d[44]),"+f"(d[45]),"+f"(d[46]),"+f"(d[47]),"+f"(d[48]),"+f"(d[49]),"+f"(d[50]),"+f"(d[51]),"+f"(d[52]),"+f"(d[53]),"+f"(d[54]),"+f"(d[55]),"+f"(d[56]),"+f"(d[57]),"+f"(d[58]),"+f"(d[59]),"+f"(d[60]),"+f"(d[61]),"+f"(d[62]),"+f"(d[63])
    : "r"(a[0]),"r"(a[1]),"r"(a[2]),"r"(a[3]),"l"(db));
} };

struct cf { float r, i; };
__device__ __forceinline__ cf cmul(cf a, cf b) { return cf{fmaf(a.r, b.r, -a.i * b.i), fmaf(a.r, b.i, a.i * b.r)}; }
__device__ __forceinline__ cf cfma(cf a, cf b, cf c) {
    return cf{fmaf(a.r, b.r, fmaf(-a.i, b.i, c.r)), fmaf(a.r, b.i, fmaf(a.i, b.r, c.i))};
}
__device__ __forceinline__ cf cexp_k(float zr, float zi, float k) {
    float e = expf(k * zr), s, c;
    sincospif(k * zi * 0.3183098861837907f, &s, &c);
    return cf{e * c, e * s};
}
constexpr int L_ = 2048, D_ = 576, P_ = 576, NST = 128;

constexpr int G1_NT = 160, G1_SEG = 40, G1_J = 20, G1_NCH = 13, G1_NSL = 9, G1_CTAS = G1_NCH * G1_NSL;
constexpr int G1_LSEG = 32, G1_LJ = 16;
constexpr int STAGES = 4;
constexpr int A_BYTES = 16384, B1_BYTES = G1_NT * 128, B2_BYTES = 144 * 128;
constexpr int NCTA = 132, G2_CTAS = 128, X5_FIRST = 84;

constexpr int KB_LBO = 128 * 16 + 16, KBB = 4 * KB_LBO;
constexpr int UB = 64 + 4096, TB = 1296;
constexpr int CHB = KBB + UB;
constexpr int CV_T = 4 * CHB, CV_BYTES = CV_T + 4 * TB;
constexpr int CV_EY = 0, CV_EX = 18432, CV_EP = 36864;

constexpr int SM_A = 0, SM_B = STAGES * A_BYTES, SM_CONV = SM_B + STAGES * B1_BYTES;
constexpr int SM_CONST = SM_CONV + CV_BYTES;
constexpr int SM_BAR = SM_CONST + 64 * 12 * 8;
constexpr int SM_XIN = SM_CONV + 25600;
constexpr int SM_XST = (SM_BAR + 384 + 1023) / 1024 * 1024;
constexpr int SM_KS = SM_XST;
constexpr int SM_TOTAL = SM_XST + 20480;
static_assert(SM_CONV % 1024 == 0 && SM_CONST % 16 == 0 && SM_XST % 1024 == 0, "align");
static_assert(SM_TOTAL <= 232448, "smem");
__device__ __forceinline__ constexpr int slot_off(int s) { return s < 4 ? SM_CONV + s * CHB : SM_A + (s - 4) * CHB; }
constexpr int BAR_FULL = 0, BAR_EPI = 32, BAR_U = 40, BAR_XTR = 48, BAR_XCH = 56, BAR_RDY = 64, BAR_XFREE = 72, BAR_EMPTY = 80, BAR_XIN = 112, BAR_HST = 120, BAR_CONVDONE = 128, BAR_HREAD = 136, BAR_U1 = 144,
              BAR_EPIGO = 152, BAR_FULL2 = 160, BAR_EMPTY2 = 192, BAR_KR = 224  , BAR_UA = 288  , BAR_G1END = 320, BAR_COUNT = 41, BAR_EPOCH = 376;

__device__ bf16 g_hT[2 * P_ * L_];
__device__ bf16 g_yT[D_ * L_];
__device__ bf16 g_xT[D_ * L_];
__device__ __align__(16) float g_gate[L_];
__device__ uint4 g_E[G1_NCH * P_];
__device__ uint32_t g_epoch, g_done, g_aux, g_xt, g_tcnt, g_hcnt[16 * 32];
constexpr int NEXP = 18;
__device__ __align__(16) uint8_t g_KB[NEXP * KBB];
__device__ __forceinline__ int sp_base(int sb) { return 4 * G1_CTAS + 7 * sb + (sb > 12 ? sb - 12 : 0); }

struct Maps { CUtensorMap x1, x1l, b1, hst, h2, cre, cim, ey, ex, xts, xin, xs3; };
struct Ptrs {
    const bf16 *u, *logA, *Aim, *Cre, *Cim, *logdt, *Dsk1, *Lre, *Lim, *Bre, *Bim, *C2re, *C2im, *logdt2, *Dsk2, *gw;
    float* out;
    int swapB;
};

__device__ __forceinline__ uint32_t mapa(uint32_t addr, uint32_t rank) {
    uint32_t r;
    asm volatile("mapa.shared::cluster.u32 %0, %1, %2;" : "=r"(r) : "r"(addr), "r"(rank));
    return r;
}
__device__ __forceinline__ void st_async_v4(uint32_t addr, uint32_t a, uint32_t b, uint32_t c, uint32_t d, uint32_t bar) {
    asm volatile("st.async.weak.shared::cluster.mbarrier::complete_tx::bytes.v4.b32 [%0], {%1,%2,%3,%4}, [%5];" ::"r"(addr), "r"(a), "r"(b), "r"(c), "r"(d), "r"(bar) : "memory");
}
__device__ __forceinline__ void st_async_v2(uint32_t addr, uint32_t a, uint32_t b, uint32_t bar) {
    asm volatile("st.async.weak.shared::cluster.mbarrier::complete_tx::bytes.v2.b32 [%0], {%1,%2}, [%3];" ::"r"(addr), "r"(a), "r"(b), "r"(bar) : "memory");
}
__device__ __forceinline__ void mbar_arrive_remote(uint32_t addr) { asm volatile("mbarrier.arrive.shared::cluster.b64 _, [%0];" ::"r"(addr) : "memory"); }
__device__ __forceinline__ void tma_st2(const CUtensorMap* m, uint32_t src, int c0, int c1) {
    asm volatile("cp.async.bulk.tensor.2d.global.shared::cta.bulk_group [%0, {%2,%3}], [%1];" ::"l"(m), "r"(src), "r"(c0), "r"(c1) : "memory");
}
__device__ __forceinline__ void red_relaxed_add(uint32_t* p, uint32_t v) {
    asm volatile("red.relaxed.gpu.global.add.u32 [%0], %1;" ::"l"(p), "r"(v) : "memory");
}
__device__ __forceinline__ void wait_counter(const uint32_t* p, uint32_t target) {
    int it = 0;
    while ((int)(ld_relaxed(p) - target) < 0) { __nanosleep(32); if (++it > WAIT_LIMIT) { DBG_TIMEOUT(32 * 8 + 8 * 0 + 248); break; } }
}
__device__ __forceinline__ void mma16816(float (&d)[4], uint32_t a0, uint32_t a1, uint32_t a2, uint32_t a3, uint32_t b0, uint32_t b1) {
    asm volatile("mma.sync.aligned.m16n8k16.row.col.f32.bf16.bf16.f32 {%0,%1,%2,%3},{%4,%5,%6,%7},{%8,%9},{%0,%1,%2,%3};"
                 : "+f"(d[0]), "+f"(d[1]), "+f"(d[2]), "+f"(d[3]) : "r"(a0), "r"(a1), "r"(a2), "r"(a3), "r"(b0), "r"(b1));
}
__device__ __forceinline__ cf csq(cf a) { return cf{fmaf(a.r, a.r, -a.i * a.i), (a.r + a.r) * a.i}; }
__device__ __forceinline__ float ex2a(float x) { float r; asm("ex2.approx.ftz.f32 %0, %1;" : "=f"(r) : "f"(x)); return r; }
__device__ __forceinline__ cf cpow_fast(float arl, float ai, float k) {
    float e = ex2a(arl * k), a = ai * k;
    return cf{e * __cosf(a), e * __sinf(a)};
}
__device__ __forceinline__ void stmatrix_x4(uint32_t addr, uint32_t r0, uint32_t r1, uint32_t r2, uint32_t r3) {
    asm volatile("stmatrix.sync.aligned.m8n8.x4.shared.b16 [%0], {%1,%2,%3,%4};" ::"r"(addr), "r"(r0), "r"(r1), "r"(r2), "r"(r3) : "memory");
}
__device__ __forceinline__ void ldmatrix_x4_trans(uint32_t addr, uint32_t& r0, uint32_t& r1, uint32_t& r2, uint32_t& r3) {
    asm volatile("ldmatrix.sync.aligned.m8n8.x4.trans.shared.b16 {%0,%1,%2,%3}, [%4];" : "=r"(r0), "=r"(r1), "=r"(r2), "=r"(r3) : "r"(addr) : "memory");
}

struct KParams { uint32_t la, im, cr, ci, ldt; };
__device__ __forceinline__ KParams kgen_load(const Ptrs& P, int ch, int t128) {
    const size_t o = (size_t)ch * NST + t128;
    KParams k;
    auto ld16 = [](const bf16* p) { uint32_t v; asm volatile("ld.global.nc.u16 %0, [%1];" : "=r"(v) : "l"(p)); return v; };
    k.la = ld16(P.logA + o); k.im = ld16(P.Aim + o); k.cr = ld16(P.Cre + o); k.ci = ld16(P.Cim + o); k.ldt = ld16(P.logdt + ch);
    return k;
}
constexpr int KS_WARP_FWD = 2304;
__device__ __forceinline__ void ldmatrix_x4(uint32_t addr, uint32_t& r0, uint32_t& r1, uint32_t& r2, uint32_t& r3) {
    asm volatile("ldmatrix.sync.aligned.m8n8.x4.shared.b16 {%0,%1,%2,%3}, [%4];" : "=r"(r0), "=r"(r1), "=r"(r2), "=r"(r3) : "r"(addr) : "memory");
}
__device__ __forceinline__ cf cis_rev(float mag_l2, float rev) {
    const float f = (rev - rintf(rev)) * 6.283185307179586f;
    const float e = ex2a(mag_l2);
    return cf{e * __cosf(f), e * __sinf(f)};
}
constexpr int KS_WARP = 16 * 144;
struct KFrag { uint32_t a[2][4][4], a2[4][2], b[4][4]; float kl; };
__device__ __forceinline__ void kgen_frags(const KParams& kraw, uint8_t* scr, int t128, KFrag& f) {
    const int w = t128 >> 5, lane = t128 & 31;
    uint32_t* rows = reinterpret_cast<uint32_t*>(scr + w * KS_WARP) + lane;
    const uint32_t su = s2u(scr + w * KS_WARP);
    const uint32_t sa = su + ((lane & 7) + 8 * ((lane >> 3) & 1)) * 144 + (lane >> 4) * 16;
    const float cr = bflo(kraw.cr), ci = bflo(kraw.ci);
    const float dt = bf16r(expf(bflo(kraw.ldt)));
    const float arl = -bf16r(expf(bflo(kraw.la))) * dt * 1.4426950408889634f;
    float rv = bflo(kraw.im) * dt * 0.15915494309189535f;
    rv -= rintf(rv);
    const cf z1 = cis_rev(arl, rv), z8 = cis_rev(8.f * arl, 8.f * rv), q1 = cis_rev(128.f * arl, 128.f * rv);
    {
        cf y{2.f * cr * dt, 2.f * ci * dt};
#pragma unroll
        for (int j = 0; j < 16; j++) {
            rows[j * 36] = pack_bf16(y.r, -y.i);
            y = cmul(y, z8);
        }
        __syncwarp();
#pragma unroll
        for (int kk = 0; kk < 4; kk++)
            ldmatrix_x4(su + ((lane & 7) + 8 * (lane >> 4)) * 144 + kk * 32 + ((lane >> 3) & 1) * 16, f.b[kk][0], f.b[kk][1], f.b[kk][2], f.b[kk][3]);
        __syncwarp();
    }
    {
        cf a{1.f, 0.f};
#pragma unroll
        for (int r = 0; r < 8; r++) {
            rows[r * 36] = pack_bf16(a.r, a.i);
            const cf x = cmul(a, q1);
            rows[(8 + r) * 36] = pack_bf16(x.r, x.i);
            a = cmul(a, z1);
        }
    }
    __syncwarp();
#pragma unroll
    for (int kk = 0; kk < 4; kk++) ldmatrix_x4(sa + kk * 32, f.a[0][kk][0], f.a[0][kk][1], f.a[0][kk][2], f.a[0][kk][3]);
    __syncwarp();
    cf q = cmul(q1, q1);
    {
        const cf z2 = cmul(z1, z1), z4 = cmul(z2, z2);
#pragma unroll
        for (int i = 0; i < 2; i++) {
            cf x = q;
#pragma unroll
            for (int a = 0; a < 4; a++) { rows[(4 * i + a) * 36] = pack_bf16(x.r, x.i); x = cmul(x, z2); }
            q = cmul(q, q1);
        }
#pragma unroll
        for (int i = 0; i < 4; i++) {
            rows[(8 + 2 * i) * 36] = pack_bf16(q.r, q.i);
            const cf x = cmul(q, z4);
            rows[(9 + 2 * i) * 36] = pack_bf16(x.r, x.i);
            q = cmul(q, q1);
        }
    }
    __syncwarp();
#pragma unroll
    for (int kk = 0; kk < 4; kk++) ldmatrix_x4(sa + kk * 32, f.a[1][kk][0], f.a[1][kk][1], f.a[1][kk][2], f.a[1][kk][3]);
    __syncwarp();
#pragma unroll
    for (int i = 0; i < 8; i++) {
        rows[i * 36] = pack_bf16(q.r, q.i);
        q = cmul(q, q1);
    }
    __syncwarp();
#pragma unroll
    for (int kk = 0; kk < 4; kk++)
        asm volatile("ldmatrix.sync.aligned.m8n8.x2.shared.b16 {%0,%1}, [%2];" : "=r"(f.a2[kk][0]), "=r"(f.a2[kk][1]) : "r"(su + (lane & 7) * 144 + kk * 32 + ((lane >> 3) & 1) * 16) : "memory");
    __syncwarp();
    float kl = 2.f * dt * (cr * q.r - ci * q.i);
#pragma unroll
    for (int o = 16; o; o >>= 1) kl += __shfl_xor_sync(~0u, kl, o);
    f.kl = kl;
}
__device__ __forceinline__ void kgen_finish(const KFrag& f, uint8_t* kbb, uint8_t* tb, int t128, int wgbar, bool gate) {
    const int w = t128 >> 5, lane = t128 & 31, g = lane >> 2, c = lane & 3;
    float acc[3][2][4];
#pragma unroll
    for (int i = 0; i < 3; i++)
#pragma unroll
        for (int j = 0; j < 2; j++) acc[i][j][0] = acc[i][j][1] = acc[i][j][2] = acc[i][j][3] = 0.f;
#pragma unroll
    for (int kk = 0; kk < 4; kk++)
#pragma unroll
        for (int mt = 0; mt < 3; mt++) {
            const uint32_t a0 = mt == 2 ? f.a2[kk][0] : f.a[mt & 1][kk][0], a2 = mt == 2 ? f.a2[kk][1] : f.a[mt & 1][kk][2];
            const uint32_t a1 = mt == 2 ? 0u : f.a[mt & 1][kk][1], a3 = mt == 2 ? 0u : f.a[mt & 1][kk][3];
            mma16816(acc[mt][0], a0, a1, a2, a3, f.b[kk][0], f.b[kk][1]);
            mma16816(acc[mt][1], a0, a1, a2, a3, f.b[kk][2], f.b[kk][3]);
        }
    if (gate) {
        float chk = 0.f;
#pragma unroll
        for (int i = 0; i < 3; i++) chk += acc[i][0][0] + acc[i][1][0];
        if (chk == 1.2345e37f) acc[0][0][1] = chk;
        bar_arrive(14, 384);
    }
    float* ps = reinterpret_cast<float*>(kbb) + lane;
    bar_sync(wgbar, 128);
    float val[20];
#pragma unroll
    for (int v = 0; v < 20; v++) {
        val[v] = v < 16 ? acc[v >> 3][(v >> 2) & 1][v & 3] : acc[2][(v >> 1) & 1][v & 1];
        if (v / 5 != w) ps[(v * 3 + ((w - v / 5 - 1) & 3)) * 32] = val[v];
    }
    float own[5];
#pragma unroll
    for (int k = 0; k < 5; k++) own[k] = w == 0 ? val[k] : (w == 1 ? val[5 + k] : (w == 2 ? val[10 + k] : val[15 + k]));
    if (lane == 0) ps[60 * 32 + w] = f.kl;
    bar_sync(wgbar, 128);
    bf16* T = reinterpret_cast<bf16*>(tb);
#pragma unroll
    for (int k = 0; k < 5; k++) {
        const int v = 5 * w + k;
        const float sum = (own[k] + ps[(v * 3) * 32]) + (ps[(v * 3 + 1) * 32] + ps[(v * 3 + 2) * 32]);
        int idx;
        if (v < 16) {
            const int mt = v >> 3, nt = (v >> 2) & 1, reg = v & 3, col = 8 * nt + 2 * c + (reg & 1), hi = reg >> 1;
            if (mt == 0) idx = 128 * hi + g + 8 * col;
            else idx = hi ? 384 + 32 * (g >> 1) + (g & 1) + 2 * col : 256 + 64 * (g >> 2) + (g & 3) + 4 * col;
        } else {
            idx = 512 + 16 * g + 8 * ((v >> 1) & 1) + 2 * c + (v & 1);
        }
        T[idx] = __float2bfloat16_rn(sum);
    }
    if (t128 == 0) T[640] = __float2bfloat16_rn((ps[60 * 32] + ps[60 * 32 + 1]) + (ps[60 * 32 + 2] + ps[60 * 32 + 3]));
    bar_sync(wgbar, 128);
    const uint16_t* T16 = reinterpret_cast<const uint16_t*>(T);
    uint8_t* kb = kbb + (3 - (lane & 3)) * KB_LBO + (126 - 2 * (lane >> 2)) * 16;
#pragma unroll 1
    for (int qq = 0; qq < 2; qq++) {
        const int qi = w + 4 * qq;
        uint4 o;
        uint32_t prev;
        if (qi == 0) {
            o = *reinterpret_cast<const uint4*>(T16 + 8 * lane);
            prev = lane ? T16[8 * lane - 1] : 0u;
        } else if (qi == 1) {
            const int i0 = 128 + 4 * (32 + lane);
            const uint2 a = *reinterpret_cast<const uint2*>(T16 + i0);
            const uint32_t e = T16[i0 + 4];
            o = make_uint4(__byte_perm(a.x, 0, 0x1010), __byte_perm(a.x, a.y, 0x5432), __byte_perm(a.y, 0, 0x1010), __byte_perm(a.y, e, 0x5432));
            prev = lane ? (a.x & 0xffffu) : T16[255];
        } else if (qi < 4) {
            const int i0 = 256 + 2 * (32 * qi + lane);
            const uint32_t a = *reinterpret_cast<const uint32_t*>(T16 + i0), e = T16[i0 + 2];
            o = make_uint4(__byte_perm(a, 0, 0x1010), a, __byte_perm(a, 0, 0x3232), __byte_perm(e, 0, 0x1010));
            prev = a & 0xffffu;
        } else {
            const int i0 = 384 + 32 * qi + lane;
            const uint32_t a = T16[i0], e = T16[i0 + 1];
            const uint32_t aa = a | (a << 16), ee = e | (e << 16);
            o = make_uint4(aa, aa, (lane & 1) ? ee : (a | (e << 16)), ee);
            prev = a;
        }
        *reinterpret_cast<uint4*>(kb - qi * 256 + 16) =
            make_uint4(__byte_perm(o.w, 0, 0x1032), __byte_perm(o.z, 0, 0x1032), __byte_perm(o.y, 0, 0x1032), __byte_perm(o.x, 0, 0x1032));
        *reinterpret_cast<uint4*>(kb - qi * 256) =
            make_uint4(__byte_perm(o.w, o.z, 0x7610), __byte_perm(o.z, o.y, 0x7610), __byte_perm(o.y, o.x, 0x7610), __byte_perm(o.x, prev, 0x5410));
    }
    fence_async_smem();
    bar_sync(wgbar, 128);
}

template <int M> struct ConvGrp {
    static __device__ __forceinline__ void load(uint32_t (&A)[2][2][4], const uint32_t* ap) {
#pragma unroll
        for (int s = 0; s < 2; s++) {
            const uint32_t* p = ap + 64 * M + 8 * s;
            A[M & 1][s][0] = p[0]; A[M & 1][s][1] = p[16]; A[M & 1][s][2] = p[4]; A[M & 1][s][3] = p[20];
        }
    }
    static __device__ __forceinline__ void go(float (&d)[64 - 4 * M], float (&fin)[64], uint32_t (&A)[2][2][4], const uint32_t* ap, uint32_t kb) {
        wg_fence();
#pragma unroll
        for (int s = 0; s < 2; s++) WgRS<128 - 8 * M>::go(d, A[M & 1][s], mkdesc(kb + 2 * s * KB_LBO + 8 * M * 16, KB_LBO, 128, 0));
        wg_commit();
        if constexpr (M + 1 < 16) ConvGrp<M + 1>::load(A, ap);
        wg_wait<0>();
        constexpr int NR = 64 - 4 * M;
#pragma unroll
        for (int i = 0; i < 4; i++) fin[NR - 4 + i] = d[NR - 4 + i];
        if constexpr (M + 1 < 16) {
            float e[NR - 4];
#pragma unroll
            for (int i = 0; i < NR - 4; i++) asm volatile("mov.b32 %0, %1;" : "=f"(e[i]) : "f"(d[i]));
            ConvGrp<M + 1>::go(e, fin, A, ap, kb);
        }
    }
};

__device__ __forceinline__ void conv_channel(int ch, uint8_t* kbb, const uint8_t* ub, int tid128, int barid) {
    const int w = tid128 >> 5, lane = tid128 & 31, g = lane >> 2, c = lane & 3;
    float d0[64], d[64];
#pragma unroll
    for (int i = 0; i < 64; i++) d0[i] = 0.f;
    uint32_t A[2][2][4];
    const uint32_t* ap = reinterpret_cast<const uint32_t*>(ub + 64) - 15 + 32 * (w & 1) + 8 * (w >> 1) + g + c;
    ConvGrp<0>::load(A, ap);
    ConvGrp<0>::go(d0, d, A, ap, s2u(kbb));
    float S[32];
#pragma unroll
    for (int j = 0; j < 16; j++) {
#pragma unroll
        for (int e = 0; e < 2; e++) {
            const float src = (c == 0) ? (j < 15 ? d[4 * (j + 1) + 2 + e] : 0.f) : d[4 * j + 2 + e];
            S[2 * j + e] = d[4 * j + e] + __shfl_sync(~0u, src, (lane & ~3) | ((c + 1) & 3));
        }
    }
    bar_sync(barid, 128);
    float2* xq = reinterpret_cast<float2*>(kbb) + (w >> 1) * 16 * 32;
    if (w & 1) {
        const int lp = (lane & ~3) | ((c + 2) & 3);
#pragma unroll
        for (int j = 0; j < 16; j++) {
            const int jp = j - (c < 2);
            if (jp >= 0) xq[jp * 32 + lp] = make_float2(S[2 * j], S[2 * j + 1]);
        }
    }
    bar_sync(barid, 128);
    if (!(w & 1)) {
        uint32_t* dst = reinterpret_cast<uint32_t*>(g_yT) + (size_t)ch * (L_ / 2) + 16 * (63 - c) + 8 * (w >> 1) + g;
#pragma unroll
        for (int j = 0; j < 16; j++) {
            float2 o = xq[j * 32 + lane];
            if (j == 15 && c >= 2) o = make_float2(0.f, 0.f);
            dst[-64 * j] = pack_bf16(S[2 * j] + o.x, S[2 * j + 1] + o.y);
        }
    }
}

__device__ __forceinline__ void scan_consts(float ldt, float Lr, float Li, bool last, int q, int c, cf* cs  ) {
    const float seg = last ? (float)G1_LSEG : (float)G1_SEG;
    const float dt = bf16r(expf(ldt));
    const float zr = dt * Lr, zi = dt * Li;
    cf* o = cs + q * 12;
    const float k3 = c == 0 ? 1.f : (c == 1 ? 2.f : 4.f * G1_NT);
#pragma unroll 1
    for (int e = 0; e < 3; e++) {
        const float k = e == 0 ? seg * c : (e == 1 ? (float)(G1_NT * c) : k3);
        const cf v = cexp_k(zr, zi, k);
        if (e < 2) o[4 + 4 * e + c] = v;
        else if (c == 0) {
            o[0] = v;
            const float nr = v.r - 1.f, ni = v.i, den = __fdividef(2.f, Lr * Lr + Li * Li);
            o[3] = cf{(nr * Lr + ni * Li) * den, (ni * Lr - nr * Li) * den};
        } else if (c < 3) o[c] = v;
    }
}

__device__ __forceinline__ cf lds_cf(const cf* p) {
    cf v;
    asm volatile("ld.shared.v2.f32 {%0,%1}, [%2];" : "=f"(v.r), "=f"(v.i) : "r"(s2u(p)));
    return v;
}
template <int RE, int IM>
__device__ __forceinline__ void scan_epilogue(float (&d)[2][80], int slice, int chunk, int tid, uint32_t tag, const cf* cs, uint8_t* stg) {
    const int w = tid >> 5, lane = tid & 31, g = lane >> 2, c = lane & 3;
    const bool last = (chunk == G1_NCH - 1);
    const int J = last ? G1_LJ : G1_J;
    const cf* o0 = cs + (8 * w + g) * 12;
    const int p0 = 64 * slice + 8 * w + g;
    cf lam[2] = {lds_cf(o0), lds_cf(o0 + 384)}, lam2[2] = {lds_cf(o0 + 1), lds_cf(o0 + 385)};
    cf T[2] = {{0.f, 0.f}, {0.f, 0.f}};
#pragma unroll
    for (int j = 0; j < G1_J; j++) {
        if (j < J) {
#pragma unroll
            for (int mt = 0; mt < 2; mt++) {
                const cf u = cfma(lam[mt], cf{d[mt][4 * j + RE], d[mt][4 * j + IM]}, cf{d[mt][4 * j + 1 + RE], d[mt][4 * j + 1 + IM]});
                d[mt][4 * j + 1 + RE] = u.r; d[mt][4 * j + 1 + IM] = u.i;
                T[mt] = cfma(lam2[mt], T[mt], u);
            }
        }
    }
    cf Pc[2];
#pragma unroll
    for (int mt = 0; mt < 2; mt++) {
        const cf* o = o0 + 384 * mt;
        cf t{__shfl_up_sync(~0u, T[mt].r, 1, 4), __shfl_up_sync(~0u, T[mt].i, 1, 4)};
        if (c >= 1) T[mt] = cfma(o[5], t, T[mt]);
        t = cf{__shfl_up_sync(~0u, T[mt].r, 2, 4), __shfl_up_sync(~0u, T[mt].i, 2, 4)};
        if (c >= 2) T[mt] = cfma(o[6], t, T[mt]);
        if (c == 3 && !last) st_pkt(&g_E[chunk * P_ + p0 + 32 * mt], T[mt].r, T[mt].i, tag);
        Pc[mt] = cf{__shfl_up_sync(~0u, T[mt].r, 1, 4), __shfl_up_sync(~0u, T[mt].i, 1, 4)};
        if (c == 0) Pc[mt] = cf{0.f, 0.f};
    }
    if (tid == 0) PROF(3);
#pragma unroll
    for (int mt = 0; mt < 2; mt++) {
        const cf G = o0[384 * mt + 3];
        Pc[mt] = cmul(G, Pc[mt]);
#pragma unroll
        for (int j = 0; j < G1_J; j++) {
            if (j < J) {
                const cf a = cmul(G, cf{d[mt][4 * j + RE], d[mt][4 * j + IM]}), b = cmul(G, cf{d[mt][4 * j + 1 + RE], d[mt][4 * j + 1 + IM]});
                d[mt][4 * j + RE] = a.r; d[mt][4 * j + IM] = a.i; d[mt][4 * j + 1 + RE] = b.r; d[mt][4 * j + 1 + IM] = b.i;
            }
        }
    }
    if (tid == 0) PROF(4);
    cf h[2];
    {
        int it = 0;
        bool ok;
        do {
            ok = true;
#pragma unroll
            for (int mt = 0; mt < 2; mt++) {
                const cf Lc4 = o0[384 * mt + 2];
                cf H{0.f, 0.f};
#pragma unroll
                for (int m = 2; m >= 0; m--) {
                    const int ip = chunk - 1 - c - 4 * m;
                    cf e{0.f, 0.f};
                    if (ip >= 0) {
                        uint64_t a, b;
                        ld_pkt(&g_E[ip * P_ + p0 + 32 * mt], a, b);
                        ok = ok && ((uint32_t)(a >> 32) == tag) && ((uint32_t)(b >> 32) == tag);
                        e = cf{__uint_as_float((uint32_t)a), __uint_as_float((uint32_t)b)};
                    }
                    H = cfma(Lc4, H, e);
                }
                h[mt] = H;
            }
            if (++it > (1 << 20)) break;
        } while (!__all_sync(~0u, ok));
#pragma unroll
        for (int mt = 0; mt < 2; mt++) {
            const cf* o = o0 + 384 * mt;
            cf H = cmul(o[8 + c], h[mt]);
            H.r += __shfl_xor_sync(~0u, H.r, 1); H.i += __shfl_xor_sync(~0u, H.i, 1);
            H.r += __shfl_xor_sync(~0u, H.r, 2); H.i += __shfl_xor_sync(~0u, H.i, 2);
            h[mt] = cfma(cmul(o[3], o[4 + c]), H, Pc[mt]);
        }
    }
    if (tid == 0) PROF(5);
    lam[0] = lds_cf(o0); lam[1] = lds_cf(o0 + 384); lam2[0] = lds_cf(o0 + 1); lam2[1] = lds_cf(o0 + 385);
    uint4* s0 = reinterpret_cast<uint4*>(stg + (16 * w + g) * 320 + (last ? 2 * G1_LSEG : 2 * G1_SEG) * c);
#pragma unroll
    for (int j4 = 0; j4 < G1_J / 4; j4++) {
        if (4 * j4 < J) {
#pragma unroll
            for (int mt = 0; mt < 2; mt++) {
                uint32_t re[4], im[4];
#pragma unroll
                for (int jj = 0; jj < 4; jj++) {
                    const int j = 4 * j4 + jj;
                    const cf he = cfma(lam[mt], h[mt], cf{d[mt][4 * j + RE], d[mt][4 * j + IM]});
                    const cf ho = cfma(lam2[mt], h[mt], cf{d[mt][4 * j + 1 + RE], d[mt][4 * j + 1 + IM]});
                    h[mt] = ho;
                    re[jj] = pack_bf16(he.r, ho.r);
                    im[jj] = pack_bf16(-he.i, -ho.i);
                }
                s0[mt * 64 * 20 + j4] = make_uint4(re[0], re[1], re[2], re[3]);
                s0[mt * 64 * 20 + 8 * 20 + j4] = make_uint4(im[0], im[1], im[2], im[3]);
            }
        }
    }
    fence_async_smem();
}

__device__ __forceinline__ float2 combine2(float y0, float y1, uint32_t xv, uint32_t av, float g, float omg, uint32_t d1, uint32_t d2) {
    const __nv_bfloat162 x2 = *reinterpret_cast<__nv_bfloat162*>(&xv);
    const __nv_bfloat162 s1 = __hmul2(x2, *reinterpret_cast<__nv_bfloat162*>(&d1));
    const __nv_bfloat162 a2 = __hadd2(*reinterpret_cast<__nv_bfloat162*>(&av), s1);
    const __nv_bfloat162 s2 = __hmul2(x2, *reinterpret_cast<__nv_bfloat162*>(&d2));
    const float ga0 = bf16r(g * __low2float(a2)), ga1 = bf16r(g * __high2float(a2));
    return make_float2(ga0 + omg * (y0 + __low2float(s2)), ga1 + omg * (y1 + __high2float(s2)));
}
__device__ __forceinline__ void ldmatrix_x2_trans(uint32_t addr, uint32_t& r0, uint32_t& r1) {
    asm volatile("ldmatrix.sync.aligned.m8n8.x2.trans.shared.b16 {%0,%1}, [%2];" : "=r"(r0), "=r"(r1) : "r"(addr) : "memory");
}
__device__ __forceinline__ void out_epilogue(uint8_t* sm, float* out, int part, int t128, int i2, int dbase) {
    const int w = t128 >> 5, lane = t128 & 31, g = lane >> 2, c = lane & 3;
    const uint8_t* blk = sm + SM_CONV;
    const uint32_t blku = s2u(blk);
#pragma unroll 1
    for (int it = part; it < 18; it += 3) {
        const int mt = it >= 9, q = it - 9 * mt;
        const int tl = mt * 64 + w * 16 + g;
        const float g0 = reinterpret_cast<const float*>(blk + CV_EP)[tl], g1 = reinterpret_cast<const float*>(blk + CV_EP)[tl + 8];
        const float om0 = bf16r(1.f - g0), om1 = bf16r(1.f - g1);
        const float4 y = reinterpret_cast<const float4*>(sm + SM_A)[it * 128 + t128];
        const uint2 ov = *reinterpret_cast<const uint2*>(sm + SM_KS + q * 2048 + t128 * 16 + mt * 8);
        const int drow = 8 * q + (lane & 7);
        const uint32_t off = mt * 9216 + drow * 128 + (((2 * w + ((lane >> 3) & 1)) ^ (drow & 7)) << 4);
        uint32_t ya, yb, xa, xc;
        ldmatrix_x2_trans(blku + CV_EY + off, ya, yb);
        ldmatrix_x2_trans(blku + CV_EX + off, xa, xc);
        const uint32_t d1 = *reinterpret_cast<const uint32_t*>(blk + CV_EP + 512 + q * 16 + 4 * c);
        const uint32_t d2 = *reinterpret_cast<const uint32_t*>(blk + CV_EP + 656 + q * 16 + 4 * c);
        const float2 r0 = combine2(y.x + bflo(ov.x), y.y + bfhi(ov.x), xa, ya, g0, om0, d1, d2);
        const float2 r1 = combine2(y.z + bflo(ov.y), y.w + bfhi(ov.y), xc, yb, g1, om1, d1, d2);
        float* o = out + (size_t)(i2 * 128 + tl) * D_ + dbase + q * 8 + 2 * c;
        *reinterpret_cast<float2*>(o) = r0;
        *reinterpret_cast<float2*>(o + 8 * D_) = r1;
    }
}

__device__ __forceinline__ void gate_job(const Ptrs& P, int row0, int lane) {
    uint4 wv[3];
#pragma unroll
    for (int k = 0; k < 3; k++) wv[k] = (lane + 32 * k < 72) ? __ldg(reinterpret_cast<const uint4*>(P.gw) + lane + 32 * k) : make_uint4(0, 0, 0, 0);
#pragma unroll 1
    for (int rr = 0; rr < 8; rr++) {
        uint4 xv[3];
#pragma unroll
        for (int k = 0; k < 3; k++) xv[k] = (lane + 32 * k < 72) ? __ldg(reinterpret_cast<const uint4*>(P.u + (size_t)(row0 + rr) * D_) + lane + 32 * k) : make_uint4(0, 0, 0, 0);
        float acc = 0.f;
#pragma unroll
        for (int k = 0; k < 3; k++) {
            const uint32_t xs[4] = {xv[k].x, xv[k].y, xv[k].z, xv[k].w}, ws[4] = {wv[k].x, wv[k].y, wv[k].z, wv[k].w};
#pragma unroll
            for (int q = 0; q < 4; q++) {
                __nv_bfloat162 pr = __hmul2(*reinterpret_cast<const __nv_bfloat162*>(&xs[q]), *reinterpret_cast<const __nv_bfloat162*>(&ws[q]));
                acc += __low2float(pr) + __high2float(pr);
            }
        }
#pragma unroll
        for (int o = 16; o; o >>= 1) acc += __shfl_xor_sync(~0u, acc, o);
        if (lane == 0) { const float sg = bf16r(acc); g_gate[row0 + rr] = bf16r(__fdividef(1.f, 1.f + __expf(-sg))); }
    }
}
__device__ __forceinline__ void transpose_job(uint32_t tile, uint32_t stg, int first, int lane) {
    const int mi = lane >> 3, i = lane & 7;
#pragma unroll 2
    for (int task = first; task < 40; task += 3) {
        const int dq = task & 1, tb = task >> 1;
        const int dg = 4 * dq + mi, row = 8 * dg + i;
        uint32_t r0, r1, r2, r3;
        ldmatrix_x4_trans(tile + (8 * tb + i) * 128 + ((dg ^ i) << 4), r0, r1, r2, r3);
        const uint32_t dst = tb < 16 ? stg + (tb >> 3) * 8192 + row * 128 + (((tb & 7) ^ (row & 7)) << 4)
                                     : stg + 16384 + row * 64 + (((tb & 3) ^ ((row >> 1) & 3)) << 4);
        stmatrix_x4(dst, r0, r1, r2, r3);
    }
    fence_async_smem();
}

constexpr int SM_SCAN = 0;
constexpr int SM_HST = 86016;

template <bool SWAP>
__global__ void __launch_bounds__(512, 1) fused_kernel(const __grid_constant__ Maps maps, const Ptrs P) {
    extern __shared__ __align__(1024) uint8_t sm[];
    const uint32_t smu = s2u(sm), bars = smu + SM_BAR;
    const int tid0 = threadIdx.x;
#define BLOCK_VARS                                                                                       \
    int b, tid;                                                                                          \
    asm volatile("mov.u32 %0, %%tid.x;" : "=r"(tid));                                                    \
    asm volatile("mov.u32 %0, %%ctaid.x;" : "=r"(b));                                                    \
    const bool has_g1 = b < G1_CTAS, has_g2 = b < G2_CTAS;                                               \
    const int chunk = b / G1_NSL, slice = b - chunk * G1_NSL;                                            \
    const int kap = b & 1, i2 = b >> 3, jd = (b >> 1) & 3, dbase = jd * 144 + kap * 72;                  \
    const bool lastc = chunk == G1_NCH - 1;                                                              \
    uint32_t epoch;                                                                                      \
    asm volatile("ld.relaxed.gpu.global.u32 %0, [%1];" : "=r"(epoch) : "l"(&g_epoch));                             \
    (void)tid; (void)has_g1; (void)has_g2; (void)slice; (void)kap; (void)i2; (void)jd; (void)dbase; (void)lastc; (void)epoch;
    if ((tid0 & 31) == 0 && (tid0 >> 5) >= 1 && (tid0 >> 5) <= 12) prefetch_map(reinterpret_cast<const CUtensorMap*>(&maps) + ((tid0 >> 5) - 1));
    if (tid0 < BAR_COUNT) {
        const bool sp = blockIdx.x >= G1_CTAS;
        mbar_init(bars + 8 * tid0, (tid0 == BAR_CONVDONE / 8 || false) ? 2 : ((tid0 == BAR_XFREE / 8 && sp) ? 4 : 1));
        fence_mbar_init();
    }
    __syncthreads();
    if (blockIdx.x < G2_CTAS) asm volatile("barrier.cluster.arrive.relaxed.aligned;" ::: "memory");
    if (tid0 == 0) { PROF(0); PROFG(16); }

    {
        uint32_t prog, cinfo;
        {
            BLOCK_VARS
            const uint32_t v = tid >> 7;
            const int sb = b - G1_CTAS;
            int nst;
            if (has_g1) {
                const uint32_t w = v - 1;
                prog = w | ((w + 2) << 4) | ((8 + w) << 8) | ((10 + w) << 12);
                nst = (v == 1 || v == 2) ? 4 : 0;
            } else if (v == 3 && sb < 12) { prog = 3u | (11u << 4); nst = 2; }
            else { prog = v | ((4 + v) << 4) | ((12 + v) << 8) | ((8 + v) << 12); nst = 4; }
            cinfo = (has_g1 ? b : sp_base(sb)) | (nst << 12) | ((uint32_t)has_g1 << 16);
        }
#pragma unroll 1
        for (int st = 0; st < (int)((cinfo >> 12) & 15); st++) {
            int tt;
            asm volatile("mov.u32 %0, %%tid.x;" : "=r"(tt));
            const int v = tt >> 7, t128 = tt & 127, op = (prog >> (4 * st)) & 15, s = op & 7;
            const bool g1 = (cinfo >> 16) & 1;
            const int chb = cinfo & 4095;
            const int ch = g1 ? chb + G1_CTAS * s : chb + s;
            if (!(op & 8)) {
                const KParams kc = kgen_load(P, ch, t128);
                KFrag fr;
                uint8_t* blk = sm + slot_off(s);
                if (g1 && st == 1) mbar_wait(bars + BAR_XTR, 0);
                kgen_frags(kc, blk, t128, fr);
                if (g1 && st == 1) {
                    bar_sync(4 + v, 128);
                    if (t128 == 0) mbar_arrive(bars + BAR_KR + 8 * (4 + s));
                    mbar_wait(bars + BAR_G1END, 0);
                }
                kgen_finish(fr, blk, sm + SM_CONV + CV_T + v * TB, t128, 4 + v, g1 && st == 0);
                if (t128 == 0) mbar_arrive(bars + BAR_KR + 8 * s);
                if (tt == 128 && st == 0) PROF(18);
            } else {
                const bool first = !((prog >> (4 * st - 4)) & 8);
                if (!g1) {
                    if (first) {
                        const int nst = (cinfo >> 12) & 15;
                        if (t128 < 32) { const int sj = (prog >> (4 * (st + (t128 >> 4)))) & 7; if (st + (t128 >> 4) < nst) reinterpret_cast<uint32_t*>(sm + slot_off(sj) + KBB)[t128 & 15] = 0u; }
                        if (t128 == 0) {
                            uint32_t epoch;
                            asm volatile("ld.relaxed.gpu.global.u32 %0, [%1];" : "=r"(epoch) : "l"(&g_epoch));
                            wait_counter(&g_xt, (epoch + 1) * G1_CTAS);
                            fence_async_smem();
                            mbar_expect(bars + BAR_UA + 8 * v, (nst - st) * 4096);
#pragma unroll 1
                            for (int j = st; j < nst; j++) {
                                const int sj = (prog >> (4 * j)) & 7;
                                bulk_ld(smu + slot_off(sj) + KBB + 64, g_xT + (size_t)(chb + sj) * L_, 4096, bars + BAR_UA + 8 * v);
                            }
                        }
                        bar_sync(4 + v, 128);
                        mbar_wait(bars + BAR_UA + 8 * v, 0);
                    }
                } else {
                    mbar_wait(bars + BAR_UA + 8 * (2 * (v - 1) + (st & 1)), 0);
                }
                if (tt == 128 && first) PROF(20);
                conv_channel(ch, sm + slot_off(s), sm + slot_off(s) + KBB, t128, 4 + v);
                bar_sync(4 + v, 128);
                if (tt == 128) PROF(first ? 22 : 23);
            }
        }
        int tid;
        asm volatile("mov.u32 %0, %%tid.x;" : "=r"(tid));
        if (!((cinfo >> 16) & 1) && (tid & 127) == 0) {
            fence_async_smem();
            mbar_arrive(bars + BAR_XFREE);
            if (tid < 128 || tid >= 384) red_release_add(&g_aux, 1);
        }
    }
    if (tid0 >= 384) {
        asm volatile("setmaxnreg.dec.sync.aligned.u32 40;");
        BLOCK_VARS
        const int warp = (tid >> 5) - 12, lane = tid & 31;
        if (warp == 0) {
            if (lane == 0) {
                const CUtensorMap* mc = kap ? &maps.cim : &maps.cre;
                if (has_g2) mbar_expect(bars + BAR_XCH, 18432);
                if (has_g1) {
                    mbar_expect(bars + BAR_XIN, 20480);
                    tma_ld2(smu + SM_XIN, &maps.xin, 64 * slice, chunk * G1_NT, bars + BAR_XIN);
#pragma unroll 1
                    for (int kb = 0; kb < 9; kb++) {
                        const int s = kb % STAGES;
                        if (kb >= STAGES) mbar_wait(bars + BAR_EMPTY + 8 * s, ((kb / STAGES) - 1) & 1);
                        mbar_expect(bars + BAR_FULL + 8 * s, A_BYTES + B1_BYTES);
                        tma_ld4(smu + SM_A + s * A_BYTES, &maps.b1, kb * 64, 0, 0, 8 * slice, bars + BAR_FULL + 8 * s);
                        tma_ld4(smu + SM_B + s * B1_BYTES, lastc ? &maps.x1l : &maps.x1, kb * 64, 0, 0, lastc ? 0 : chunk * (G1_NT / 2), bars + BAR_FULL + 8 * s);
                    }
                }
                if (has_g2) {
                    if (has_g1) mbar_wait(bars + BAR_G1END, 0);
#pragma unroll 1
                    for (int kb = 0; kb < STAGES; kb++) {
                        mbar_expect(bars + BAR_FULL2 + 8 * kb, A_BYTES + B2_BYTES);
                        tma_ld2(smu + SM_B + kb * B1_BYTES, mc, kb * 64, jd * 144, bars + BAR_FULL2 + 8 * kb);
                    }
                    const int c0 = (i2 * 128) / G1_NT, c1 = (i2 * 128 + 127) / G1_NT;
                    {
                        int it = 0;
                        const uint32_t tgt = (epoch + 1) * G1_NSL;
                        while (true) {
                            const uint32_t v0 = ld_relaxed(&g_hcnt[c0 * 32]), v1 = ld_relaxed(&g_hcnt[c1 * 32]);
                            if ((int)(v0 - tgt) >= 0 && (int)(v1 - tgt) >= 0) break;
                            if (++it > WAIT_LIMIT) break;
                        }
                    }
                    mbar_wait(bars + (has_g1 ? BAR_HREAD : BAR_XFREE), 0);
                    PROF(8);
#pragma unroll 1
                    for (int kb = 0; kb < 9; kb++) {
                        const int s = kb % STAGES;
                        if (kb >= STAGES) {
                            mbar_wait(bars + BAR_EMPTY2 + 8 * s, ((kb / STAGES) - 1) & 1);
                            mbar_expect(bars + BAR_FULL2 + 8 * s, A_BYTES + B2_BYTES);
                            tma_ld2(smu + SM_B + s * B1_BYTES, mc, kb * 64, jd * 144, bars + BAR_FULL2 + 8 * s);
                        }
                        tma_ld2(smu + SM_A + s * A_BYTES, &maps.h2, i2 * 128, kap * P_ + kb * 64, bars + BAR_FULL2 + 8 * s);
                        tma_ld2(smu + SM_A + s * A_BYTES + 8192, &maps.h2, i2 * 128 + 64, kap * P_ + kb * 64, bars + BAR_FULL2 + 8 * s);
                    }
                }
            }
            __syncwarp();
            if (has_g2) asm volatile("barrier.cluster.wait.acquire.aligned;" ::: "memory");
        } else {
            if (has_g1) {
                if (tid == 416) PROF(27);
                mbar_wait(bars + BAR_XIN, 0);
                if (tid == 416) PROF(28);
                transpose_job(smu + SM_XIN, smu + SM_XST, warp - 1, lane);
                if (tid == 416) PROF(29);
                bar_sync(3, 96);
                if (tid == 416) PROF(30);
            }
            if (warp == 2 && has_g2) {
                gate_job(P, 16 * b, lane);
                __syncwarp();
                if (lane == 0) red_release_add(&g_aux, 1);
            }
            if (warp != 2 && has_g1) {
              if (lane == 0) {
                if (warp == 1) {
                    mbar_arrive(bars + BAR_XTR);
                    tma_st2(&maps.xts, smu + SM_XST, chunk * G1_NT, 64 * slice);
                    tma_st2(&maps.xts, smu + SM_XST + 8192, chunk * G1_NT + 64, 64 * slice);
                    if (!lastc) tma_st2(&maps.xs3, smu + SM_XST + 16384, chunk * G1_NT + 128, 64 * slice);
                } else {
                    mbar_wait(bars + BAR_HST, 0);
                    tma_st4(&maps.hst, smu + SM_A, chunk * G1_NT, 0, 0, 8 * slice);
                }
                bulk_commit();
                bulk_wait0();
                red_relaxed_add(warp == 1 ? &g_xt : &g_hcnt[chunk * 32], 1);
                mbar_arrive(bars + (warp == 1 ? BAR_XFREE : BAR_HREAD));
                PROF(warp == 1 ? 17 : 7);
              }
            }
            if (warp == 1 && has_g1) {
                __syncwarp();
                if (lane == 0) wait_counter(&g_xt, (epoch + 1) * G1_CTAS);
#pragma unroll 1
                for (int i = 0; i < 4; i++) {
                    mbar_wait(bars + BAR_KR + 8 * (i < 2 ? i : 4 + i), 0);
                    if (lane < 16) reinterpret_cast<uint32_t*>(sm + slot_off(i) + KBB)[lane] = 0u;
                    __syncwarp();
                    if (lane == 0) {
                        const uint32_t ub = bars + BAR_UA + 8 * (2 * (i & 1) + (i >> 1));
                        fence_async_smem();
                        mbar_expect(ub, 4096);
                        bulk_ld(smu + slot_off(i) + KBB + 64, g_xT + (size_t)(b + G1_CTAS * i) * L_, 4096, ub);
                    }
                }
            }
            if (warp == 1 && has_g2) {
                __syncwarp();
                gate_job(P, 16 * b + 8, lane);
                __syncwarp();
                if (lane == 0) red_release_add(&g_aux, 1);
            }
            __syncwarp();
            if (has_g2) asm volatile("barrier.cluster.wait.acquire.aligned;" ::: "memory");
            if (warp == 2 && has_g2 && lane == 0) {
                mbar_wait(bars + BAR_CONVDONE, 0);
                if (!has_g1) mbar_wait(bars + BAR_XFREE, 0);
                mbar_arrive_remote(mapa(bars + BAR_RDY, kap ^ 1));
                wait_counter(&g_aux, (epoch + 1) * (2 * NCTA + 2 * (NCTA - G1_CTAS) + 2 * G2_CTAS));
                asm volatile("fence.acq_rel.gpu;" ::: "memory");
                fence_async_smem();
                const uint32_t blk = smu + SM_CONV;
                mbar_expect(bars + BAR_EPI, 4 * 9216 + 512 + 288);
#pragma unroll 1
                for (int i = 0; i < 4; i++) tma_ld2(blk + i * 9216, i < 2 ? &maps.ey : &maps.ex, i2 * 128 + 64 * (i & 1), dbase, bars + BAR_EPI);
                bulk_ld(blk + CV_EP, g_gate + i2 * 128, 512, bars + BAR_EPI);
                bulk_ld(blk + CV_EP + 512, P.Dsk1 + dbase, 144, bars + BAR_EPI);
                bulk_ld(blk + CV_EP + 656, P.Dsk2 + dbase, 144, bars + BAR_EPI);
                PROF(26);
            }
        }
    } else if (tid0 >= 128) {
        {
            BLOCK_VARS
            const int t128 = tid & 127;
            if (has_g2) asm volatile("barrier.cluster.wait.acquire.aligned;" ::: "memory");
            if (t128 == 0) {
                mbar_arrive(bars + BAR_CONVDONE);
                red_release_add(&g_aux, 1);
                PROF(25);
            }
            if (has_g2) {
                mbar_wait(bars + BAR_EPI, 0);
                mbar_wait(bars + BAR_XCH, 0);
                mbar_wait(bars + BAR_EPIGO, 0);
                out_epilogue(sm, P.out, tid >> 7, t128, i2, dbase);
            }
        }
    } else {
        asm volatile("setmaxnreg.inc.sync.aligned.u32 216;");
        BLOCK_VARS
        if (has_g1) {
            {
                cf* cs = reinterpret_cast<cf*>(sm + SM_CONST);
                const int p0 = 64 * slice + (tid >> 2);
                float pl[2] = {ldbf(P.logdt2 + p0), ldbf(P.logdt2 + p0 + 32)}, pr[2] = {ldbf(P.Lre + p0), ldbf(P.Lre + p0 + 32)}, pi[2] = {ldbf(P.Lim + p0), ldbf(P.Lim + p0 + 32)};
#pragma unroll 1
                for (int r = 0; r < 2; r++) scan_consts(r ? pl[1] : pl[0], r ? pr[1] : pr[0], r ? pi[1] : pi[0], lastc, 32 * r + (tid >> 2), tid & 3, cs);
            }
            bar_sync(14, 384);
            float d[2][80];
#pragma unroll
            for (int i = 0; i < 80; i++) { d[0][i] = 0.f; d[1][i] = 0.f; }
#pragma unroll 1
            for (int kb = 0; kb < 9; kb++) {
                const int s = kb % STAGES;
                mbar_wait(bars + BAR_FULL + 8 * s, (kb / STAGES) & 1);
                if (tid == 0 && kb == 0) PROF(1);
                wg_fence();
                const uint32_t a = smu + SM_A + s * A_BYTES, bb = smu + SM_B + s * B1_BYTES;
#pragma unroll
                for (int k = 0; k < 4; k++) {
                    wgmma_ss_n160<0, 0>(d[0], mkdesc(a + k * 32, 16, 1024, 1), mkdesc(bb + k * 32, 16, 1024, 1), 1);
                    wgmma_ss_n160<0, 0>(d[1], mkdesc(a + 8192 + k * 32, 16, 1024, 1), mkdesc(bb + k * 32, 16, 1024, 1), 1);
                }
                wg_commit();
                if (kb > 0) {
                    wg_wait<1>();
                    if (tid == 0) mbar_arrive(bars + BAR_EMPTY + 8 * ((kb - 1) % STAGES));
                }
            }
            wg_wait<0>();
            if (tid == 0) PROF(2);
            if (tid == 0) mbar_arrive(bars + BAR_G1END);
            scan_epilogue<SWAP ? 2 : 0, SWAP ? 0 : 2>(d, slice, chunk, tid, epoch + 1, reinterpret_cast<const cf*>(sm + SM_CONST), sm + SM_A);
            asm volatile("barrier.cluster.wait.acquire.aligned;" ::: "memory");
            bar_sync(1, 128);
            if (tid == 0) { mbar_arrive(bars + BAR_HST); PROF(6); }
        } else if (has_g2) {
            asm volatile("barrier.cluster.wait.acquire.aligned;" ::: "memory");
        }
        if (has_g2) {
            float d[2][72];
#pragma unroll
            for (int i = 0; i < 72; i++) { d[0][i] = 0.f; d[1][i] = 0.f; }
#pragma unroll 1
            for (int kb = 0; kb < 9; kb++) {
                const int s = kb % STAGES;
                mbar_wait(bars + BAR_FULL2 + 8 * s, (kb / STAGES) & 1);
                if (tid == 0 && kb == 0) PROF(9);
                wg_fence();
                const uint32_t a = smu + SM_A + s * A_BYTES, bb = smu + SM_B + s * B1_BYTES;
#pragma unroll
                for (int k = 0; k < 4; k++) {
                    wgmma_ss_n144<1, 0>(d[0], mkdesc(a + k * 2048, 8192, 1024, 1), mkdesc(bb + k * 32, 16, 1024, 1), 1);
                    wgmma_ss_n144<1, 0>(d[1], mkdesc(a + 8192 + k * 2048, 8192, 1024, 1), mkdesc(bb + k * 32, 16, 1024, 1), 1);
                }
                wg_commit();
                if (kb > 0) {
                    wg_wait<1>();
                    if (tid == 0) mbar_arrive(bars + BAR_EMPTY2 + 8 * ((kb - 1) % STAGES));
                }
            }
            wg_wait<0>();
            if (tid == 0) PROF(10);
            mbar_wait(bars + BAR_RDY, 0);
            const uint32_t rem = mapa(smu + SM_KS, kap ^ 1) + tid * 16, rbar = mapa(bars + BAR_XCH, kap ^ 1);
            float4* own = reinterpret_cast<float4*>(sm + SM_A) + tid;
            if (kap) {
#pragma unroll
                for (int q = 0; q < 9; q++)
                    st_async_v4(rem + q * 2048, pack_bf16(d[0][4 * q], d[0][4 * q + 1]), pack_bf16(d[0][4 * q + 2], d[0][4 * q + 3]),
                                pack_bf16(d[1][4 * q], d[1][4 * q + 1]), pack_bf16(d[1][4 * q + 2], d[1][4 * q + 3]), rbar);
#pragma unroll
                for (int q = 0; q < 9; q++) {
                    own[q * 128] = make_float4(d[0][36 + 4 * q], d[0][37 + 4 * q], d[0][38 + 4 * q], d[0][39 + 4 * q]);
                    own[(9 + q) * 128] = make_float4(d[1][36 + 4 * q], d[1][37 + 4 * q], d[1][38 + 4 * q], d[1][39 + 4 * q]);
                }
            } else {
#pragma unroll
                for (int q = 0; q < 9; q++)
                    st_async_v4(rem + q * 2048, pack_bf16(d[0][36 + 4 * q], d[0][37 + 4 * q]), pack_bf16(d[0][38 + 4 * q], d[0][39 + 4 * q]),
                                pack_bf16(d[1][36 + 4 * q], d[1][37 + 4 * q]), pack_bf16(d[1][38 + 4 * q], d[1][39 + 4 * q]), rbar);
#pragma unroll
                for (int q = 0; q < 9; q++) {
                    own[q * 128] = make_float4(d[0][4 * q], d[0][4 * q + 1], d[0][4 * q + 2], d[0][4 * q + 3]);
                    own[(9 + q) * 128] = make_float4(d[1][4 * q], d[1][4 * q + 1], d[1][4 * q + 2], d[1][4 * q + 3]);
                }
            }
            bar_sync(1, 128);
            if (tid == 0) mbar_arrive(bars + BAR_EPIGO);
            mbar_wait(bars + BAR_EPI, 0);
            if (tid == 0) PROF(11);
            mbar_wait(bars + BAR_XCH, 0);
            if (tid == 0) PROF(12);
            out_epilogue(sm, P.out, 0, tid, i2, dbase);
            if (tid == 0) PROF(13);
        }
        if (tid == 0) {
            if (atomicAdd(&g_done, 1) == NCTA - 1) { g_done = 0; __threadfence(); g_epoch = epoch + 1; }
        }
    }
}
typedef CUresult (*EncFn)(CUtensorMap*, CUtensorMapDataType, cuuint32_t, void*, const cuuint64_t*, const cuuint64_t*, const cuuint32_t*,
                          const cuuint32_t*, CUtensorMapInterleave, CUtensorMapSwizzle, CUtensorMapL2promotion, CUtensorMapFloatOOBfill);

bool enc_map(EncFn enc, CUtensorMap* m, const void* base, int rank, const uint64_t* dims, const uint64_t* strides, const uint32_t* box,
             CUtensorMapSwizzle swz) {
    cuuint64_t gd[5], gs[5];
    cuuint32_t bd[5], es[5];
    for (int i = 0; i < rank; i++) { gd[i] = dims[i]; bd[i] = box[i]; es[i] = 1; }
    for (int i = 0; i + 1 < rank; i++) gs[i] = strides[i];
    return enc(m, CU_TENSOR_MAP_DATA_TYPE_BFLOAT16, rank, const_cast<void*>(base), gd, gs, bd, es, CU_TENSOR_MAP_INTERLEAVE_NONE, swz,
               CU_TENSOR_MAP_L2_PROMOTION_L2_256B, CU_TENSOR_MAP_FLOAT_OOB_FILL_NONE) == CUDA_SUCCESS;
}

}

extern "C" void kernel_launch(void* const* d_in, const int* in_sizes, int n_in, void* d_out, int out_size) {
    (void)in_sizes; (void)n_in; (void)out_size;
    static EncFn enc = nullptr;
    static void *hT = nullptr, *yT = nullptr, *xT = nullptr;
    if (!enc) {
        void* fn = nullptr;
        cudaDriverEntryPointQueryResult qr;
        cudaGetDriverEntryPoint("cuTensorMapEncodeTiled", &fn, cudaEnableDefault, &qr);
        enc = (EncFn)fn;
        cudaGetSymbolAddress(&hT, g_hT);
        cudaGetSymbolAddress(&yT, g_yT);
        cudaGetSymbolAddress(&xT, g_xT);
        cudaFuncSetAttribute(fused_kernel<false>, cudaFuncAttributeMaxDynamicSharedMemorySize, SM_TOTAL);
        cudaFuncSetAttribute(fused_kernel<true>, cudaFuncAttributeMaxDynamicSharedMemorySize, SM_TOTAL);
    }
    Ptrs P;
    P.u = (const bf16*)d_in[0]; P.logA = (const bf16*)d_in[1]; P.Aim = (const bf16*)d_in[2]; P.Cre = (const bf16*)d_in[3];
    P.Cim = (const bf16*)d_in[4]; P.logdt = (const bf16*)d_in[5]; P.Dsk1 = (const bf16*)d_in[6];
    P.Lre = (const bf16*)d_in[8]; P.Lim = (const bf16*)d_in[9]; P.Bre = (const bf16*)d_in[10]; P.Bim = (const bf16*)d_in[11];
    P.C2re = (const bf16*)d_in[12]; P.C2im = (const bf16*)d_in[13]; P.logdt2 = (const bf16*)d_in[14]; P.Dsk2 = (const bf16*)d_in[15];
    P.gw = (const bf16*)d_in[16];
    P.out = (float*)d_out;
    P.swapB = (uintptr_t)P.Bim < (uintptr_t)P.Bre;
    Maps maps;
    bool ok = true;
    const uint64_t RB = D_ * 2;
    {
        uint64_t dims[4] = {D_, 2, 4, L_ / 2}, st[3] = {RB, G1_SEG * RB, 2 * RB};
        uint32_t box[4] = {64, 2, 4, G1_J};
        ok &= enc_map(enc, &maps.x1, P.u, 4, dims, st, box, CU_TENSOR_MAP_SWIZZLE_128B);
        uint64_t dims2[4] = {D_, 2, 4, G1_LJ}, st2[3] = {RB, G1_LSEG * RB, 2 * RB};
        ok &= enc_map(enc, &maps.x1l, P.u + (size_t)(G1_NCH - 1) * G1_NT * D_, 4, dims2, st2, box, CU_TENSOR_MAP_SWIZZLE_128B);
    }
    {
        const bf16* lo = P.swapB ? P.Bim : P.Bre;
        const bf16* hi = P.swapB ? P.Bre : P.Bim;
        uint64_t dims[4] = {D_, 8, 2, P_ / 8}, st[3] = {RB, (uint64_t)((const char*)hi - (const char*)lo), 8 * RB};
        uint32_t box[4] = {64, 8, 2, 8};
        ok &= enc_map(enc, &maps.b1, lo, 4, dims, st, box, CU_TENSOR_MAP_SWIZZLE_128B);
    }
    {
        uint64_t dims[4] = {L_, 8, 2, P_ / 8}, st[3] = {L_ * 2, (uint64_t)P_ * L_ * 2, 8 * L_ * 2};
        uint32_t box[4] = {G1_NT, 8, 2, 8};
        ok &= enc_map(enc, &maps.hst, hT, 4, dims, st, box, CU_TENSOR_MAP_SWIZZLE_NONE);
    }
    {
        uint64_t dims[2] = {L_, 2 * P_}, st[1] = {L_ * 2};
        uint32_t box[2] = {64, 64};
        ok &= enc_map(enc, &maps.h2, hT, 2, dims, st, box, CU_TENSOR_MAP_SWIZZLE_128B);
        uint64_t dc[2] = {P_, D_}, sc[1] = {(uint64_t)P_ * 2};
        uint32_t bc[2] = {64, 144};
        ok &= enc_map(enc, &maps.cre, P.C2re, 2, dc, sc, bc, CU_TENSOR_MAP_SWIZZLE_128B);
        ok &= enc_map(enc, &maps.cim, P.C2im, 2, dc, sc, bc, CU_TENSOR_MAP_SWIZZLE_128B);
        uint64_t dy[2] = {L_, D_}, sy[1] = {L_ * 2};
        uint32_t by[2] = {64, 72};
        ok &= enc_map(enc, &maps.ey, yT, 2, dy, sy, by, CU_TENSOR_MAP_SWIZZLE_128B);
        ok &= enc_map(enc, &maps.ex, xT, 2, dy, sy, by, CU_TENSOR_MAP_SWIZZLE_128B);
        uint32_t bt[2] = {64, 64}, bt2[2] = {32, 64};
        ok &= enc_map(enc, &maps.xts, xT, 2, dy, sy, bt, CU_TENSOR_MAP_SWIZZLE_128B);
        ok &= enc_map(enc, &maps.xs3, xT, 2, dy, sy, bt2, CU_TENSOR_MAP_SWIZZLE_64B);
        uint64_t dx[2] = {D_, L_}, sx[1] = {RB};
        uint32_t bx[2] = {64, G1_NT};
        ok &= enc_map(enc, &maps.xin, P.u, 2, dx, sx, bx, CU_TENSOR_MAP_SWIZZLE_128B);
    }
    if (!ok) return;
    cudaLaunchConfig_t cfg = {};
    cfg.gridDim = dim3(NCTA); cfg.blockDim = dim3(512); cfg.dynamicSmemBytes = SM_TOTAL; cfg.stream = cudaStreamPerThread;
    cudaLaunchAttribute at[1];
    at[0].id = cudaLaunchAttributeClusterDimension; at[0].val.clusterDim.x = 2; at[0].val.clusterDim.y = 1; at[0].val.clusterDim.z = 1;
    cfg.attrs = at; cfg.numAttrs = 1;
    if (P.swapB) cudaLaunchKernelEx(&cfg, fused_kernel<true>, maps, P);
    else cudaLaunchKernelEx(&cfg, fused_kernel<false>, maps, P);
}
```
